```python
import torch

def _softmax(x, axis=-1):
    return torch.softmax(x, dim=axis)
def _gelu(x):
    return torch.nn.functional.gelu(x, approximate="tanh")
def _silu(x):
    return torch.nn.functional.silu(x)
def _sigmoid(x):
    return torch.sigmoid(x)
def _layernorm(x, axis=-1, eps=1e-5):
    m = x.mean(dim=axis, keepdim=True)
    v = x.var(dim=axis, keepdim=True, unbiased=False)
    return (x - m) / torch.sqrt(v + eps)
def _scatter_add(tgt, idx, src, axis=0):
    return tgt.clone().index_add_(axis, idx, src)
def _segment_sum(src, seg, n):
    out = torch.zeros((n,) + src.shape[1:], dtype=src.dtype)
    return out.index_add_(0, seg, src)
def _pad(x, pw):
    flat = tuple(v for pair in reversed(pw) for v in pair)
    return torch.nn.functional.pad(x, flat)

kernel_name = 'concat_heads__linear_kernel_hedgehog__ssm_conv_s5__prompt'

def setup_inputs():

    _w = (lambda a: (lambda t: t.to(torch.bfloat16) if t.is_floating_point() else t)(torch.as_tensor(a)))
    def _A_setup():
        B, S, D, H = 1, 2048, 576, 32
        Dh = D // H
        return {
            "x": _w((lambda *s: torch.randn(*s, dtype=torch.bfloat16) * 0.4)(B, S, D)),
            "wqkv": _w((lambda *s: torch.randn(*s, dtype=torch.bfloat16) * 0.4)(D, 3 * D)),
            "w_phi": _w((lambda *s: torch.randn(*s, dtype=torch.bfloat16) * 0.4)(H, Dh, Dh) * (Dh ** -0.5)),
            "wo": _w((lambda *s: torch.randn(*s, dtype=torch.bfloat16) * 0.05)(D, D)),
        }
    _A_in = _A_setup()

    def _B_setup():
        B, S, D = 1, 2048, 576
        P = D
        Lambda_re = -0.5 * (lambda _x: torch.exp(torch.as_tensor(_x)))((lambda *s: torch.randn(*s, dtype=torch.bfloat16) * 0.8)(P))
        Lambda_im = (lambda *s: torch.randn(*s, dtype=torch.bfloat16) * 0.8)(P) * 1.0
        B_re = (lambda *s: torch.randn(*s, dtype=torch.bfloat16) * 0.8)(P, D) * (D ** -0.5)
        B_im = (lambda *s: torch.randn(*s, dtype=torch.bfloat16) * 0.8)(P, D) * (D ** -0.5)
        C_re = (lambda *s: torch.randn(*s, dtype=torch.bfloat16) * 0.8)(D, P) * (P ** -0.5)
        C_im = (lambda *s: torch.randn(*s, dtype=torch.bfloat16) * 0.8)(D, P) * (P ** -0.5)
        log_dt = (lambda *s: torch.randn(*s, dtype=torch.bfloat16) * 0.8)(P) * 0.3 - 2.0
        Dskip = (lambda *s: torch.randn(*s, dtype=torch.bfloat16) * 0.8)(D)
        return {
            "x": _w((lambda *s: torch.randn(*s, dtype=torch.bfloat16) * 0.05)(B, S, D)),
            "Lambda_re": _w(Lambda_re),
            "Lambda_im": _w(Lambda_im),
            "B_re": _w(B_re),
            "B_im": _w(B_im),
            "C_re": _w(C_re),
            "C_im": _w(C_im),
            "log_dt": _w(log_dt),
            "Dskip": _w(Dskip),
        }
    _B_in = _B_setup()

    return {
        "A_x": _A_in["x"],
        "A_wqkv": _A_in["wqkv"],
        "A_w_phi": _A_in["w_phi"],
        "A_wo": _A_in["wo"],
        "B_x": _B_in["x"],
        "B_Lambda_re": _B_in["Lambda_re"],
        "B_Lambda_im": _B_in["Lambda_im"],
        "B_B_re": _B_in["B_re"],
        "B_B_im": _B_in["B_im"],
        "B_C_re": _B_in["C_re"],
        "B_C_im": _B_in["C_im"],
        "B_log_dt": _B_in["log_dt"],
        "B_Dskip": _B_in["Dskip"],
    }

def reference(A_x, A_wqkv, A_w_phi, A_wo, B_x, B_Lambda_re, B_Lambda_im, B_B_re, B_B_im, B_C_re, B_C_im, B_log_dt, B_Dskip):
    def _A_ref(x, wqkv, w_phi, wo):
        B, S, D = x.shape
        H = 32; Dh = D // H
        qkv = (lambda x, *d: x.permute(*d))((x @ wqkv).reshape(B, S, 3, H, Dh), 2, 0, 3, 1, 4)
        q, k, v = qkv[0], qkv[1], qkv[2]
        pq = torch.einsum("bhsd,hdf->bhsf", q, w_phi)
        pk = torch.einsum("bhsd,hdf->bhsf", k, w_phi)
        phi_q = torch.concatenate([_softmax(pq, axis=-1), _softmax(-pq, axis=-1)], axis=-1)
        phi_k = torch.concatenate([_softmax(pk, axis=-1), _softmax(-pk, axis=-1)], axis=-1)
        kv = torch.einsum("bhsf,bhsd->bhfd", phi_k, v)
        z  = torch.einsum("bhsf->bhf", phi_k)
        num = torch.einsum("bhqf,bhfd->bhqd", phi_q, kv)
        den = torch.einsum("bhqf,bhf->bhq", phi_q, z)[..., None] + 1e-6
        o = num / den
        return (lambda x, *d: x.permute(*d))(o, 0, 2, 1, 3).reshape(B, S, D) @ wo

    def _B_ref(x, Lambda_re, Lambda_im, B_re, B_im, C_re, C_im, log_dt, Dskip):
        Bsz, L, H = x.shape
        Lam = Lambda_re + 1j * Lambda_im
        Bmat = B_re + 1j * B_im
        Cmat = C_re + 1j * C_im
        dt = torch.exp(log_dt)
        Lam_bar = torch.exp(dt * Lam)
        B_bar = ((Lam_bar - 1.0) / Lam)[:, None] * Bmat
        Bu = torch.einsum("bld,pd->blp", x + 0j, B_bar)
        h = torch.zeros_like(Bu[:, 0, :])
        hs = []
        for t in range(L):
            h = Lam_bar[None, :] * h + Bu[:, t, :]
            hs.append(h)
        hseq = torch.stack(hs, 1)
        y = 2.0 * torch.einsum("blp,dp->bld", hseq, Cmat).real + x * Dskip[None, None, :]
        return y

    a = _A_ref(A_x, A_wqkv, A_w_phi, A_wo)
    b = _B_ref(B_x, B_Lambda_re, B_Lambda_im, B_B_re, B_B_im, B_C_re, B_C_im, B_log_dt, B_Dskip)
    return torch.concatenate([a, b], axis=-1)
```

```cpp
#include <cuda_runtime.h>
#include <cuda.h>
#include <cuda_bf16.h>
#include <stdint.h>

typedef unsigned long long u64;
template <int TA, int TB, int O, int L> __device__ __forceinline__ void wg64(float (&d)[L], uint32_t alo, uint32_t ahi, uint32_t blo, uint32_t bhi, uint32_t acc) {
    asm volatile("{ .reg .pred p; .reg .b64 da, db; setp.ne.u32 p, %36, 0; mov.b64 da, {%32, %33}; mov.b64 db, {%34, %35};\n"
        "wgmma.mma_async.sync.aligned.m64n64k16.f32.bf16.bf16 {%0, %1, %2, %3, %4, %5, %6, %7, %8, %9, %10, %11, %12, %13, %14, %15, %16, %17, %18, %19, %20, %21, %22, %23, %24, %25, %26, %27, %28, %29, %30, %31}, da, db, p, 1, 1, %37, %38; }"
        : "+f"(d[O + 0]), "+f"(d[O + 1]), "+f"(d[O + 2]), "+f"(d[O + 3]), "+f"(d[O + 4]), "+f"(d[O + 5]), "+f"(d[O + 6]), "+f"(d[O + 7]), "+f"(d[O + 8]), "+f"(d[O + 9]), "+f"(d[O + 10]), "+f"(d[O + 11]), "+f"(d[O + 12]), "+f"(d[O + 13]), "+f"(d[O + 14]), "+f"(d[O + 15]), "+f"(d[O + 16]), "+f"(d[O + 17]), "+f"(d[O + 18]), "+f"(d[O + 19]), "+f"(d[O + 20]), "+f"(d[O + 21]), "+f"(d[O + 22]), "+f"(d[O + 23]), "+f"(d[O + 24]), "+f"(d[O + 25]), "+f"(d[O + 26]), "+f"(d[O + 27]), "+f"(d[O + 28]), "+f"(d[O + 29]), "+f"(d[O + 30]), "+f"(d[O + 31]) : "r"(alo), "r"(ahi), "r"(blo), "r"(bhi), "r"(acc), "n"(TA), "n"(TB));
}
template <int TA, int TB, int O, int L> __device__ __forceinline__ void wg72(float (&d)[L], uint32_t alo, uint32_t ahi, uint32_t blo, uint32_t bhi, uint32_t acc) {
    asm volatile("{ .reg .pred p; .reg .b64 da, db; setp.ne.u32 p, %40, 0; mov.b64 da, {%36, %37}; mov.b64 db, {%38, %39};\n"
        "wgmma.mma_async.sync.aligned.m64n72k16.f32.bf16.bf16 {%0, %1, %2, %3, %4, %5, %6, %7, %8, %9, %10, %11, %12, %13, %14, %15, %16, %17, %18, %19, %20, %21, %22, %23, %24, %25, %26, %27, %28, %29, %30, %31, %32, %33, %34, %35}, da, db, p, 1, 1, %41, %42; }"
        : "+f"(d[O + 0]), "+f"(d[O + 1]), "+f"(d[O + 2]), "+f"(d[O + 3]), "+f"(d[O + 4]), "+f"(d[O + 5]), "+f"(d[O + 6]), "+f"(d[O + 7]), "+f"(d[O + 8]), "+f"(d[O + 9]), "+f"(d[O + 10]), "+f"(d[O + 11]), "+f"(d[O + 12]), "+f"(d[O + 13]), "+f"(d[O + 14]), "+f"(d[O + 15]), "+f"(d[O + 16]), "+f"(d[O + 17]), "+f"(d[O + 18]), "+f"(d[O + 19]), "+f"(d[O + 20]), "+f"(d[O + 21]), "+f"(d[O + 22]), "+f"(d[O + 23]), "+f"(d[O + 24]), "+f"(d[O + 25]), "+f"(d[O + 26]), "+f"(d[O + 27]), "+f"(d[O + 28]), "+f"(d[O + 29]), "+f"(d[O + 30]), "+f"(d[O + 31]), "+f"(d[O + 32]), "+f"(d[O + 33]), "+f"(d[O + 34]), "+f"(d[O + 35]) : "r"(alo), "r"(ahi), "r"(blo), "r"(bhi), "r"(acc), "n"(TA), "n"(TB));
}
template <int TA, int TB, int O, int L> __device__ __forceinline__ void wg96(float (&d)[L], uint32_t alo, uint32_t ahi, uint32_t blo, uint32_t bhi, uint32_t acc) {
    asm volatile("{ .reg .pred p; .reg .b64 da, db; setp.ne.u32 p, %52, 0; mov.b64 da, {%48, %49}; mov.b64 db, {%50, %51};\n"
        "wgmma.mma_async.sync.aligned.m64n96k16.f32.bf16.bf16 {%0, %1, %2, %3, %4, %5, %6, %7, %8, %9, %10, %11, %12, %13, %14, %15, %16, %17, %18, %19, %20, %21, %22, %23, %24, %25, %26, %27, %28, %29, %30, %31, %32, %33, %34, %35, %36, %37, %38, %39, %40, %41, %42, %43, %44, %45, %46, %47}, da, db, p, 1, 1, %53, %54; }"
        : "+f"(d[O + 0]), "+f"(d[O + 1]), "+f"(d[O + 2]), "+f"(d[O + 3]), "+f"(d[O + 4]), "+f"(d[O + 5]), "+f"(d[O + 6]), "+f"(d[O + 7]), "+f"(d[O + 8]), "+f"(d[O + 9]), "+f"(d[O + 10]), "+f"(d[O + 11]), "+f"(d[O + 12]), "+f"(d[O + 13]), "+f"(d[O + 14]), "+f"(d[O + 15]), "+f"(d[O + 16]), "+f"(d[O + 17]), "+f"(d[O + 18]), "+f"(d[O + 19]), "+f"(d[O + 20]), "+f"(d[O + 21]), "+f"(d[O + 22]), "+f"(d[O + 23]), "+f"(d[O + 24]), "+f"(d[O + 25]), "+f"(d[O + 26]), "+f"(d[O + 27]), "+f"(d[O + 28]), "+f"(d[O + 29]), "+f"(d[O + 30]), "+f"(d[O + 31]), "+f"(d[O + 32]), "+f"(d[O + 33]), "+f"(d[O + 34]), "+f"(d[O + 35]), "+f"(d[O + 36]), "+f"(d[O + 37]), "+f"(d[O + 38]), "+f"(d[O + 39]), "+f"(d[O + 40]), "+f"(d[O + 41]), "+f"(d[O + 42]), "+f"(d[O + 43]), "+f"(d[O + 44]), "+f"(d[O + 45]), "+f"(d[O + 46]), "+f"(d[O + 47]) : "r"(alo), "r"(ahi), "r"(blo), "r"(bhi), "r"(acc), "n"(TA), "n"(TB));
}
template <int TA, int TB, int O, int L> __device__ __forceinline__ void wg128(float (&d)[L], uint32_t alo, uint32_t ahi, uint32_t blo, uint32_t bhi, uint32_t acc) {
    asm volatile("{ .reg .pred p; .reg .b64 da, db; setp.ne.u32 p, %68, 0; mov.b64 da, {%64, %65}; mov.b64 db, {%66, %67};\n"
        "wgmma.mma_async.sync.aligned.m64n128k16.f32.bf16.bf16 {%0, %1, %2, %3, %4, %5, %6, %7, %8, %9, %10, %11, %12, %13, %14, %15, %16, %17, %18, %19, %20, %21, %22, %23, %24, %25, %26, %27, %28, %29, %30, %31, %32, %33, %34, %35, %36, %37, %38, %39, %40, %41, %42, %43, %44, %45, %46, %47, %48, %49, %50, %51, %52, %53, %54, %55, %56, %57, %58, %59, %60, %61, %62, %63}, da, db, p, 1, 1, %69, %70; }"
        : "+f"(d[O + 0]), "+f"(d[O + 1]), "+f"(d[O + 2]), "+f"(d[O + 3]), "+f"(d[O + 4]), "+f"(d[O + 5]), "+f"(d[O + 6]), "+f"(d[O + 7]), "+f"(d[O + 8]), "+f"(d[O + 9]), "+f"(d[O + 10]), "+f"(d[O + 11]), "+f"(d[O + 12]), "+f"(d[O + 13]), "+f"(d[O + 14]), "+f"(d[O + 15]), "+f"(d[O + 16]), "+f"(d[O + 17]), "+f"(d[O + 18]), "+f"(d[O + 19]), "+f"(d[O + 20]), "+f"(d[O + 21]), "+f"(d[O + 22]), "+f"(d[O + 23]), "+f"(d[O + 24]), "+f"(d[O + 25]), "+f"(d[O + 26]), "+f"(d[O + 27]), "+f"(d[O + 28]), "+f"(d[O + 29]), "+f"(d[O + 30]), "+f"(d[O + 31]), "+f"(d[O + 32]), "+f"(d[O + 33]), "+f"(d[O + 34]), "+f"(d[O + 35]), "+f"(d[O + 36]), "+f"(d[O + 37]), "+f"(d[O + 38]), "+f"(d[O + 39]), "+f"(d[O + 40]), "+f"(d[O + 41]), "+f"(d[O + 42]), "+f"(d[O + 43]), "+f"(d[O + 44]), "+f"(d[O + 45]), "+f"(d[O + 46]), "+f"(d[O + 47]), "+f"(d[O + 48]), "+f"(d[O + 49]), "+f"(d[O + 50]), "+f"(d[O + 51]), "+f"(d[O + 52]), "+f"(d[O + 53]), "+f"(d[O + 54]), "+f"(d[O + 55]), "+f"(d[O + 56]), "+f"(d[O + 57]), "+f"(d[O + 58]), "+f"(d[O + 59]), "+f"(d[O + 60]), "+f"(d[O + 61]), "+f"(d[O + 62]), "+f"(d[O + 63]) : "r"(alo), "r"(ahi), "r"(blo), "r"(bhi), "r"(acc), "n"(TA), "n"(TB));
}
template <int TA, int TB, int O, int L> __device__ __forceinline__ void wg144(float (&d)[L], uint32_t alo, uint32_t ahi, uint32_t blo, uint32_t bhi, uint32_t acc) {
    asm volatile("{ .reg .pred p; .reg .b64 da, db; setp.ne.u32 p, %76, 0; mov.b64 da, {%72, %73}; mov.b64 db, {%74, %75};\n"
        "wgmma.mma_async.sync.aligned.m64n144k16.f32.bf16.bf16 {%0, %1, %2, %3, %4, %5, %6, %7, %8, %9, %10, %11, %12, %13, %14, %15, %16, %17, %18, %19, %20, %21, %22, %23, %24, %25, %26, %27, %28, %29, %30, %31, %32, %33, %34, %35, %36, %37, %38, %39, %40, %41, %42, %43, %44, %45, %46, %47, %48, %49, %50, %51, %52, %53, %54, %55, %56, %57, %58, %59, %60, %61, %62, %63, %64, %65, %66, %67, %68, %69, %70, %71}, da, db, p, 1, 1, %77, %78; }"
        : "+f"(d[O + 0]), "+f"(d[O + 1]), "+f"(d[O + 2]), "+f"(d[O + 3]), "+f"(d[O + 4]), "+f"(d[O + 5]), "+f"(d[O + 6]), "+f"(d[O + 7]), "+f"(d[O + 8]), "+f"(d[O + 9]), "+f"(d[O + 10]), "+f"(d[O + 11]), "+f"(d[O + 12]), "+f"(d[O + 13]), "+f"(d[O + 14]), "+f"(d[O + 15]), "+f"(d[O + 16]), "+f"(d[O + 17]), "+f"(d[O + 18]), "+f"(d[O + 19]), "+f"(d[O + 20]), "+f"(d[O + 21]), "+f"(d[O + 22]), "+f"(d[O + 23]), "+f"(d[O + 24]), "+f"(d[O + 25]), "+f"(d[O + 26]), "+f"(d[O + 27]), "+f"(d[O + 28]), "+f"(d[O + 29]), "+f"(d[O + 30]), "+f"(d[O + 31]), "+f"(d[O + 32]), "+f"(d[O + 33]), "+f"(d[O + 34]), "+f"(d[O + 35]), "+f"(d[O + 36]), "+f"(d[O + 37]), "+f"(d[O + 38]), "+f"(d[O + 39]), "+f"(d[O + 40]), "+f"(d[O + 41]), "+f"(d[O + 42]), "+f"(d[O + 43]), "+f"(d[O + 44]), "+f"(d[O + 45]), "+f"(d[O + 46]), "+f"(d[O + 47]), "+f"(d[O + 48]), "+f"(d[O + 49]), "+f"(d[O + 50]), "+f"(d[O + 51]), "+f"(d[O + 52]), "+f"(d[O + 53]), "+f"(d[O + 54]), "+f"(d[O + 55]), "+f"(d[O + 56]), "+f"(d[O + 57]), "+f"(d[O + 58]), "+f"(d[O + 59]), "+f"(d[O + 60]), "+f"(d[O + 61]), "+f"(d[O + 62]), "+f"(d[O + 63]), "+f"(d[O + 64]), "+f"(d[O + 65]), "+f"(d[O + 66]), "+f"(d[O + 67]), "+f"(d[O + 68]), "+f"(d[O + 69]), "+f"(d[O + 70]), "+f"(d[O + 71]) : "r"(alo), "r"(ahi), "r"(blo), "r"(bhi), "r"(acc), "n"(TA), "n"(TB));
}
template <int TA, int TB, int O, int L> __device__ __forceinline__ void wg160(float (&d)[L], uint32_t alo, uint32_t ahi, uint32_t blo, uint32_t bhi, uint32_t acc) {
    asm volatile("{ .reg .pred p; .reg .b64 da, db; setp.ne.u32 p, %84, 0; mov.b64 da, {%80, %81}; mov.b64 db, {%82, %83};\n"
        "wgmma.mma_async.sync.aligned.m64n160k16.f32.bf16.bf16 {%0, %1, %2, %3, %4, %5, %6, %7, %8, %9, %10, %11, %12, %13, %14, %15, %16, %17, %18, %19, %20, %21, %22, %23, %24, %25, %26, %27, %28, %29, %30, %31, %32, %33, %34, %35, %36, %37, %38, %39, %40, %41, %42, %43, %44, %45, %46, %47, %48, %49, %50, %51, %52, %53, %54, %55, %56, %57, %58, %59, %60, %61, %62, %63, %64, %65, %66, %67, %68, %69, %70, %71, %72, %73, %74, %75, %76, %77, %78, %79}, da, db, p, 1, 1, %85, %86; }"
        : "+f"(d[O + 0]), "+f"(d[O + 1]), "+f"(d[O + 2]), "+f"(d[O + 3]), "+f"(d[O + 4]), "+f"(d[O + 5]), "+f"(d[O + 6]), "+f"(d[O + 7]), "+f"(d[O + 8]), "+f"(d[O + 9]), "+f"(d[O + 10]), "+f"(d[O + 11]), "+f"(d[O + 12]), "+f"(d[O + 13]), "+f"(d[O + 14]), "+f"(d[O + 15]), "+f"(d[O + 16]), "+f"(d[O + 17]), "+f"(d[O + 18]), "+f"(d[O + 19]), "+f"(d[O + 20]), "+f"(d[O + 21]), "+f"(d[O + 22]), "+f"(d[O + 23]), "+f"(d[O + 24]), "+f"(d[O + 25]), "+f"(d[O + 26]), "+f"(d[O + 27]), "+f"(d[O + 28]), "+f"(d[O + 29]), "+f"(d[O + 30]), "+f"(d[O + 31]), "+f"(d[O + 32]), "+f"(d[O + 33]), "+f"(d[O + 34]), "+f"(d[O + 35]), "+f"(d[O + 36]), "+f"(d[O + 37]), "+f"(d[O + 38]), "+f"(d[O + 39]), "+f"(d[O + 40]), "+f"(d[O + 41]), "+f"(d[O + 42]), "+f"(d[O + 43]), "+f"(d[O + 44]), "+f"(d[O + 45]), "+f"(d[O + 46]), "+f"(d[O + 47]), "+f"(d[O + 48]), "+f"(d[O + 49]), "+f"(d[O + 50]), "+f"(d[O + 51]), "+f"(d[O + 52]), "+f"(d[O + 53]), "+f"(d[O + 54]), "+f"(d[O + 55]), "+f"(d[O + 56]), "+f"(d[O + 57]), "+f"(d[O + 58]), "+f"(d[O + 59]), "+f"(d[O + 60]), "+f"(d[O + 61]), "+f"(d[O + 62]), "+f"(d[O + 63]), "+f"(d[O + 64]), "+f"(d[O + 65]), "+f"(d[O + 66]), "+f"(d[O + 67]), "+f"(d[O + 68]), "+f"(d[O + 69]), "+f"(d[O + 70]), "+f"(d[O + 71]), "+f"(d[O + 72]), "+f"(d[O + 73]), "+f"(d[O + 74]), "+f"(d[O + 75]), "+f"(d[O + 76]), "+f"(d[O + 77]), "+f"(d[O + 78]), "+f"(d[O + 79]) : "r"(alo), "r"(ahi), "r"(blo), "r"(bhi), "r"(acc), "n"(TA), "n"(TB));
}
__device__ __forceinline__ void wgrs80(float (&d)[40], uint32_t a0, uint32_t a1, uint32_t a2, uint32_t a3, uint32_t blo, uint32_t bhi, uint32_t acc) {
    asm volatile("{ .reg .pred p; .reg .b64 db; setp.ne.u32 p, %46, 0; mov.b64 db, {%44, %45};\n"
        "wgmma.mma_async.sync.aligned.m64n80k16.f32.bf16.bf16 {%0, %1, %2, %3, %4, %5, %6, %7, %8, %9, %10, %11, %12, %13, %14, %15, %16, %17, %18, %19, %20, %21, %22, %23, %24, %25, %26, %27, %28, %29, %30, %31, %32, %33, %34, %35, %36, %37, %38, %39}, {%40, %41, %42, %43}, db, p, 1, 1, 0; }"
        : "+f"(d[0]), "+f"(d[1]), "+f"(d[2]), "+f"(d[3]), "+f"(d[4]), "+f"(d[5]), "+f"(d[6]), "+f"(d[7]), "+f"(d[8]), "+f"(d[9]), "+f"(d[10]), "+f"(d[11]), "+f"(d[12]), "+f"(d[13]), "+f"(d[14]), "+f"(d[15]), "+f"(d[16]), "+f"(d[17]), "+f"(d[18]), "+f"(d[19]), "+f"(d[20]), "+f"(d[21]), "+f"(d[22]), "+f"(d[23]), "+f"(d[24]), "+f"(d[25]), "+f"(d[26]), "+f"(d[27]), "+f"(d[28]), "+f"(d[29]), "+f"(d[30]), "+f"(d[31]), "+f"(d[32]), "+f"(d[33]), "+f"(d[34]), "+f"(d[35]), "+f"(d[36]), "+f"(d[37]), "+f"(d[38]), "+f"(d[39]) : "r"(a0), "r"(a1), "r"(a2), "r"(a3), "r"(blo), "r"(bhi), "r"(acc));
}

__device__ uint4 g_wimg[2 * 108 * 576];
__device__ float4 g_kvacc[2][32 * 180];
__device__ u64 g_agg[2][32 * 576];
__device__ unsigned g_cnt[20 * 32];
__device__ unsigned g_epoch;
#define CNT_K 0
#define CNT_WO 4
#define CNT_KV 6

#define PST(i)
#define PSTP(i)

struct __align__(64) Params {
    CUtensorMap m[10];
    const uint32_t* wqkv; const unsigned short* wphi; const uint32_t* wo;
    const uint2* xb; const unsigned short* lre; const unsigned short* lim; const unsigned short* ldt; const uint2* dsk;
    float* out; int swap;
};

#define SB0 0x400u
#define BAR 230400u
#define A_AUX 110592u
#define A_PHI (A_AUX + 21504u)
#define A_X 156672u
#define B_HD 122880u
#define B_X 155648u
#define B_RECV (B_HD + 9u * 8192u)
#define R1(s) (16u * (s))
#define R2(s) (128u + 16u * (s))
#define TOK(i) (320u + 8u * (i))
#define SIG(i) (384u + 8u * (i))
#define KVD(i) (424u + 8u * (i))
#define NUMD(i) (440u + 8u * (i))
#define BXD(i) (424u + 8u * (i))
#define HR(i) (440u + 8u * (i))
#define EPO 512u
#define RDY(i) (520u + 8u * (i))
#define KVR(i) (536u + 8u * (i))
#define PART(i) (568u + 8u * (i))
#define RFULL(i) (520u + 8u * (i))
#define VST(i) (640u + 8u * (i))
#define RFREE(i) (640u + 8u * (i))
#define XD(i) (664u + 8u * (i))
#define DONE 680u
#define FSIG 688u
#define EPOVAL 696u

#define DHI_SW 0x40000040u

__device__ __forceinline__ void mb_init(uint32_t bar, uint32_t cnt) { asm volatile("mbarrier.init.shared::cta.b64 [%0], %1;" :: "r"(bar), "r"(cnt) : "memory"); }
__device__ __forceinline__ void mb_expect(uint32_t bar, uint32_t bytes) { asm volatile("mbarrier.arrive.expect_tx.shared::cta.b64 _, [%0], %1;" :: "r"(bar), "r"(bytes) : "memory"); }
__device__ __forceinline__ void mb_arrive(uint32_t bar) { asm volatile("mbarrier.arrive.shared::cta.b64 _, [%0];" :: "r"(bar) : "memory"); }
__device__ __forceinline__ void mb_arrive_n(uint32_t bar, uint32_t n) { asm volatile("mbarrier.arrive.shared::cta.b64 _, [%0], %1;" :: "r"(bar), "r"(n) : "memory"); }
__device__ __forceinline__ void mb_arrive_rem(uint32_t bar, uint32_t n) { asm volatile("mbarrier.arrive.shared::cluster.b64 _, [%0], %1;" :: "r"(bar), "r"(n) : "memory"); }
__device__ __forceinline__ void mb_wait(uint32_t bar, uint32_t parity) {
    asm volatile("{ .reg .pred p;\n LW: mbarrier.try_wait.parity.shared::cta.b64 p, [%0], %1;\n @!p bra LW; }" :: "r"(bar), "r"(parity) : "memory");
}
__device__ __forceinline__ void mb_wait_cl(uint32_t bar, uint32_t parity) {
    asm volatile("{ .reg .pred p;\n LW: mbarrier.try_wait.parity.acquire.cluster.shared::cta.b64 p, [%0], %1;\n @!p bra LW; }" :: "r"(bar), "r"(parity) : "memory");
}
__device__ __forceinline__ void mb_wait_b(uint32_t bar) {
    asm volatile("{ .reg .pred p; .reg .u32 c; mov.u32 c, 0;\n"
                 "LW: mbarrier.try_wait.parity.shared::cta.b64 p, [%0], 0, 1000;\n"
                 "@p bra LD;\n add.u32 c, c, 1; setp.lt.u32 p, c, 200000; @p bra LW; trap;\n LD: }" :: "r"(bar) : "memory");
}
__device__ __forceinline__ void wg_fence() { asm volatile("wgmma.fence.sync.aligned;" ::: "memory"); }
__device__ __forceinline__ void wg_commit() { asm volatile("wgmma.commit_group.sync.aligned;" ::: "memory"); }
template <int N> __device__ __forceinline__ void wg_wait() { asm volatile("wgmma.wait_group.sync.aligned %0;" :: "n"(N) : "memory"); }
template <int L> __device__ __forceinline__ void reg_fence(float (&d)[L]) {
#pragma unroll
    for (int i = 0; i < L; i++) asm volatile("" : "+f"(d[i]) :: "memory");
}
template <int L> __device__ __forceinline__ void reg_def(float (&d)[L]) {
#pragma unroll
    for (int i = 0; i < L; i++) asm volatile("{ .reg .f32 t; mov.f32 %0, t; }" : "=f"(d[i]));
}
__device__ __forceinline__ void proxy_fence() { asm volatile("fence.proxy.async.shared::cta;" ::: "memory"); }
__device__ __forceinline__ void proxy_fence_g() { asm volatile("fence.proxy.async.global;" ::: "memory"); }
__device__ __forceinline__ void wg_bar(int wg) { asm volatile("bar.sync %0, 128;" :: "r"(wg + 1) : "memory"); }
__device__ __forceinline__ bool elect_one() { uint32_t p; asm volatile("{ .reg .pred P; elect.sync _|P, 0xffffffff; selp.u32 %0, 1, 0, P; }" : "=r"(p)); return p; }
__device__ __forceinline__ void cl_arrive() { asm volatile("barrier.cluster.arrive.relaxed.aligned;" ::: "memory"); }
__device__ __forceinline__ void cl_wait() { asm volatile("barrier.cluster.wait.aligned;" ::: "memory"); }
__device__ __forceinline__ uint32_t pack2(float lo, float hi) { uint32_t r; asm("cvt.rn.bf16x2.f32 %0, %1, %2;" : "=r"(r) : "f"(hi), "f"(lo)); return r; }
__device__ __forceinline__ float ex2f(float x) { float r; asm("ex2.approx.ftz.f32 %0, %1;" : "=f"(r) : "f"(x)); return r; }
__device__ __forceinline__ float rcpf(float x) { float r; asm("rcp.approx.ftz.f32 %0, %1;" : "=f"(r) : "f"(x)); return r; }
__device__ __forceinline__ void sts128(uint32_t a, uint32_t x, uint32_t y, uint32_t z, uint32_t w) { asm volatile("st.shared.v4.b32 [%0], {%1, %2, %3, %4};" :: "r"(a), "r"(x), "r"(y), "r"(z), "r"(w) : "memory"); }
__device__ __forceinline__ void sts64(uint32_t a, uint32_t x, uint32_t y) { asm volatile("st.shared.v2.b32 [%0], {%1, %2};" :: "r"(a), "r"(x), "r"(y) : "memory"); }
__device__ __forceinline__ void stsm4(uint32_t a, uint32_t x, uint32_t y, uint32_t z, uint32_t w) { asm volatile("stmatrix.sync.aligned.m8n8.x4.shared.b16 [%0], {%1, %2, %3, %4};" :: "r"(a), "r"(x), "r"(y), "r"(z), "r"(w) : "memory"); }
__device__ __forceinline__ void stsm2(uint32_t a, uint32_t x, uint32_t y) { asm volatile("stmatrix.sync.aligned.m8n8.x2.shared.b16 [%0], {%1, %2};" :: "r"(a), "r"(x), "r"(y) : "memory"); }
#define EL "{ .reg .pred p; elect.sync _|p, 0xffffffff;\n @p "
__device__ __forceinline__ void e_init(uint32_t bar, uint32_t cnt) { asm volatile(EL "mbarrier.init.shared::cta.b64 [%0], %1; }" :: "r"(bar), "r"(cnt) : "memory"); }
__device__ __forceinline__ void e_expect(uint32_t bar, uint32_t bytes) { asm volatile(EL "mbarrier.arrive.expect_tx.shared::cta.b64 _, [%0], %1; }" :: "r"(bar), "r"(bytes) : "memory"); }
__device__ __forceinline__ void e_arrive(uint32_t bar, uint32_t n) { asm volatile(EL "mbarrier.arrive.shared::cta.b64 _, [%0], %1; }" :: "r"(bar), "r"(n) : "memory"); }
__device__ __forceinline__ void tma2(uint32_t dst, const CUtensorMap* m, uint32_t bar, int a, int b) {
    asm volatile(EL "cp.async.bulk.tensor.2d.shared::cluster.global.mbarrier::complete_tx::bytes [%0], [%1, {%3, %4}], [%2]; }" :: "r"(dst), "l"(m), "r"(bar), "r"(a), "r"(b) : "memory"); }
__device__ __forceinline__ void tma3(uint32_t dst, const CUtensorMap* m, uint32_t bar, int a, int b, int c) {
    asm volatile(EL "cp.async.bulk.tensor.3d.shared::cluster.global.mbarrier::complete_tx::bytes [%0], [%1, {%3, %4, %5}], [%2]; }" :: "r"(dst), "l"(m), "r"(bar), "r"(a), "r"(b), "r"(c) : "memory"); }
__device__ __forceinline__ void tma4(uint32_t dst, const CUtensorMap* m, uint32_t bar, int a, int d) {
    asm volatile(EL "cp.async.bulk.tensor.4d.shared::cluster.global.mbarrier::complete_tx::bytes [%0], [%1, {%3, %5, %5, %4}], [%2]; }" :: "r"(dst), "l"(m), "r"(bar), "r"(a), "r"(d), "r"(0) : "memory"); }
__device__ __forceinline__ void tma5(uint32_t dst, const CUtensorMap* m, uint32_t bar, int a, int e) {
    asm volatile(EL "cp.async.bulk.tensor.5d.shared::cluster.global.mbarrier::complete_tx::bytes [%0], [%1, {%3, %5, %5, %5, %4}], [%2]; }" :: "r"(dst), "l"(m), "r"(bar), "r"(a), "r"(e), "r"(0) : "memory"); }
__device__ __forceinline__ void bulk_g2s(uint32_t dst, const void* src, uint32_t bar, uint32_t bytes) {
    asm volatile(EL "cp.async.bulk.shared::cluster.global.mbarrier::complete_tx::bytes [%0], [%1], %3, [%2]; }" :: "r"(dst), "l"(src), "r"(bar), "r"(bytes) : "memory"); }
__device__ __forceinline__ void bulk_s2s(uint32_t dst, uint32_t src, uint32_t bar, uint32_t bytes) {
    asm volatile(EL "cp.async.bulk.shared::cluster.shared::cta.mbarrier::complete_tx::bytes [%0], [%1], %3, [%2]; }" :: "r"(dst), "r"(src), "r"(bar), "r"(bytes) : "memory"); }
__device__ __forceinline__ void pf_map(const CUtensorMap* m) { asm volatile(EL "prefetch.tensormap [%0]; }" :: "l"(m) : "memory"); }
__device__ __forceinline__ void poll_ge(const unsigned* p, unsigned target) {
    for (;;) {
        unsigned v; asm volatile("ld.acquire.gpu.global.u32 %0, [%1];" : "=r"(v) : "l"(p) : "memory");
        if (__all_sync(0xffffffffu, (int)(v - target) >= 0)) break;
    }
}
__device__ __forceinline__ void signal_cnt(unsigned* p) { asm volatile(EL "red.release.gpu.global.add.u32 [%0], 1; }" :: "l"(p) : "memory"); }
__device__ __forceinline__ uint32_t read_epoch(uint32_t bb) {
    uint32_t e;
    asm volatile("ld.relaxed.gpu.global.u32 %0, [%1];" : "=r"(e) : "l"(&g_epoch) : "memory");
    asm volatile("st.shared.u32 [%0], %1;" :: "r"(bb + EPOVAL), "r"(e) : "memory");
    __syncwarp();
    e_arrive(bb + EPO, 1);
    return e;
}
__device__ __forceinline__ uint32_t get_epoch(uint32_t bb) { mb_wait(bb + EPO, 0); uint32_t e; asm volatile("ld.shared.u32 %0, [%1];" : "=r"(e) : "r"(bb + EPOVAL) : "memory"); return e; }

template <int O, int L> __device__ __forceinline__ void softmax_row(const float (&a)[L], uint32_t (&pp)[9], uint32_t (&pn)[9]) {
    float mx = fmaxf(a[O], a[O + 1]), mn = fminf(a[O], a[O + 1]);
#pragma unroll
    for (int j = 1; j < 9; j++) { mx = fmaxf(mx, fmaxf(a[O + 4 * j], a[O + 4 * j + 1])); mn = fminf(mn, fminf(a[O + 4 * j], a[O + 4 * j + 1])); }
    float ep[18], en[18];
#pragma unroll
    for (int j = 0; j < 9; j++) {
        ep[2 * j] = ex2f(a[O + 4 * j] - mx); ep[2 * j + 1] = ex2f(a[O + 4 * j + 1] - mx);
        en[2 * j] = ex2f(mn - a[O + 4 * j]); en[2 * j + 1] = ex2f(mn - a[O + 4 * j + 1]);
    }
    float s0 = ep[0], s1 = ep[1], t0 = en[0], t1 = en[1];
#pragma unroll
    for (int j = 1; j < 9; j++) { s0 += ep[2 * j]; s1 += ep[2 * j + 1]; t0 += en[2 * j]; t1 += en[2 * j + 1]; }
    const float rp = rcpf(s0 + s1), rn = rcpf(t0 + t1);
#pragma unroll
    for (int j = 0; j < 9; j++) { pp[j] = pack2(ep[2 * j] * rp, ep[2 * j + 1] * rp); pn[j] = pack2(en[2 * j] * rn, en[2 * j + 1] * rn); }
}

struct cf { float x, y; };
__device__ __forceinline__ cf cmul(cf a, cf b) { return {fmaf(a.x, b.x, -a.y * b.y), fmaf(a.x, b.y, a.y * b.x)}; }
__device__ __forceinline__ cf csq(cf a) { return {fmaf(a.x, a.x, -a.y * a.y), 2.f * a.x * a.y}; }
__device__ __forceinline__ cf cfma(cf a, cf b, cf c) { return {fmaf(a.x, b.x, fmaf(-a.y, b.y, c.x)), fmaf(a.x, b.y, fmaf(a.y, b.x, c.y))}; }
__device__ __forceinline__ cf csel(bool p, cf a, cf b) { return {p ? a.x : b.x, p ? a.y : b.y}; }
__device__ __forceinline__ float bf2f(unsigned short h) { return __uint_as_float((uint32_t)h << 16); }

__device__ __forceinline__ void a_producer(const Params& P, uint32_t sb, int pw, int c, int tile) {
    const uint32_t bb = sb + BAR;
    if (pw < 2) {
        int slot = pw + 3; uint32_t par = 1;
        const int a0 = c ? 25 : 18, a1 = c ? 23 : 20, tc = c ? 1440 : 1408;
        const CUtensorMap* mt = &P.m[2 + c];
#pragma unroll 1
        for (int it = pw; it < 18; it += 2) {
            const uint32_t bar = bb + R1(slot), dst = sb + slot * 20480;
            mb_wait(bar + 8, par);
            e_expect(bar, pw ? 20480 : 20480 + 8192);
            if (pw == 0) tma2(sb + A_X + it * 4096, &P.m[0], bar, it * 32, tile * 64);
            tma3(dst, &P.m[1], bar, 0, it * 32, a0);
            tma3(dst + 8192, &P.m[1], bar, 0, it * 32, a1);
            tma2(dst + 16384, mt, bar, tc, it * 32);
            slot += 2; if (slot >= 7) { slot -= 7; par ^= 1; }
        }
        const uint8_t* src = (const uint8_t*)g_wimg + (size_t)(c * 108 + pw) * 9216;
        par = 1;
#pragma unroll 1
        for (int r = 0; r < 9; r++) {
            if (r == 0 || r == 3) { mb_wait(bb + RDY(r & 1), 0); proxy_fence_g(); }
#pragma unroll 1
            for (int s = pw; s < 12; s += 2) {
                const uint32_t bar = bb + R2(s);
                mb_wait(r ? bar + 8 : bb + R1(((9 * s + 8) * 52) >> 10) + 8, r ? par : 0);
                e_expect(bar, 9216); bulk_g2s(sb + s * 9216, src, bar, 9216); src += 2 * 9216;
            }
            par ^= 1;
        }
    } else if (pw == 2) {
        const int lane = threadIdx.x & 31;
        const unsigned e = read_epoch(bb) + 1;
        poll_ge(&g_cnt[(CNT_K + 2 * c + (lane & 1)) * 32], 16 * e);
        e_arrive(bb + RDY(0), 1); PSTP(1);
        poll_ge(&g_cnt[(CNT_WO + c) * 32], 32 * e);
        e_arrive(bb + RDY(1), 1); PSTP(2);
#pragma unroll 1
        for (int tq = 0; tq < 4; tq++) { poll_ge(&g_cnt[(CNT_KV + 4 * c + (tq ^ (2 * c))) * 32], 32 * e); e_arrive(bb + KVR(tq), 1); PSTP(3 + tq); }
        if (blockIdx.x == 0) {
            poll_ge(&g_cnt[min(lane, 5) * 32], (lane < 4 ? 16 : 32) * e);
            asm volatile(EL "st.relaxed.gpu.global.u32 [%0], %1; }" :: "l"(&g_epoch), "r"(e) : "memory");
        }
    } else {
#pragma unroll
        for (int i = 0; i < 4; i++) e_expect(bb + PART(2 * i + 1), 9216);
        mb_wait_b(bb + EPO);
#pragma unroll 1
        for (int i = 0; i < 5; i++) { mb_wait_b(bb + SIG(i)); signal_cnt(&g_cnt[(i ? CNT_KV + 4 * c + ((i - 1) ^ (2 * c)) : CNT_WO + c) * 32]); PSTP(7 + i); }
    }
}

template <int NB, int L> __device__ __forceinline__ void v_mainloop(float (&acc)[L], uint32_t bb, uint32_t boff, bool lead) {
    int slot = 3; uint32_t par = 0, prev = 0;
    uint32_t alo = (SB0 + A_X) >> 4;
    reg_def(acc);
#pragma unroll 1
    for (int kc = 0; kc < 9; kc++) {
#pragma unroll
        for (int h = 0; h < 2; h++) {
            const uint32_t bar = bb + R1(slot), blo = ((SB0 + boff + slot * 20480) >> 4) | (256u << 16);
            mb_wait(bar, par);
            wg_fence();
            if (NB == 128) { wg128<0, 1, 0>(acc, alo + 4 * h, DHI_SW, blo, DHI_SW, h | kc); wg128<0, 1, 0>(acc, alo + 4 * h + 2, DHI_SW, blo + 128, DHI_SW, 1); }
            else { wg160<0, 1, 0>(acc, alo + 4 * h, DHI_SW, blo, DHI_SW, h | kc); wg160<0, 1, 0>(acc, alo + 4 * h + 2, DHI_SW, blo + 128, DHI_SW, 1); }
            wg_commit();
            wg_wait<1>();
            if (lead && (h | kc)) mb_arrive(prev);
            prev = bar + 8;
            if (++slot == 7) { slot = 0; par ^= 1; }
        }
        alo += 512;
    }
    wg_wait<0>(); reg_fence(acc);
    if (lead) mb_arrive(prev);
}

template <int KIND> __device__ __forceinline__ void n_mainloop(float (&acc)[72], uint32_t bb, uint32_t rb, int T, bool lead) {
    int slot = 3 * ((0x186c8 >> (2 * T)) & 3); uint32_t par = (0xae >> T) & 1, prev = 0;
    const bool oa = T >= 6;
    uint32_t alo = ((SB0 + A_X) >> 4) | (oa ? 64u << 16 : 0u), inc = oa ? 256 : 4;
    const uint32_t ahi = oa ? 8u : DHI_SW, ks = oa ? 128 : 2, dx = oa ? 0 : 504, tok = bb + TOK(min(T, 7));
    constexpr int NB = KIND ? 3 : 6;
#pragma unroll 1
    for (int blk = 0; blk < NB; blk++) {
        if (KIND == 0 && oa) {
            const int p0 = blk + (blk >= 1) + (blk >= 4);
            mb_wait(bb + PART(p0), 0);
            mb_wait(bb + PART(p0 | (blk == 0 || blk == 3)), 0);
        }
#pragma unroll
        for (int h = 0; h < 3; h++) {
            const uint32_t bar = bb + R2(slot + h), blo = ((SB0 + (slot + h) * 9216) >> 4) | (8u << 16);
            mb_wait(bar, par);
            if (h == 2 && blk == NB - 1 && lead) mb_arrive(tok);
            wg_fence();
            if (KIND == 0) {
                wg144<0, 0, 0>(acc, alo, ahi, blo, 16, h | blk);
                wg144<0, 0, 0>(acc, alo + ks, ahi, blo + 288, 16, 1);
                alo += inc; inc ^= dx;
            } else {
                wg72<0, 0, 0>(acc, alo, ahi, blo, 16, h | blk);
                wg72<0, 0, 0>(acc, alo + ks, ahi, blo + 144, 16, 1);
                wg72<0, 0, 0>(acc, alo + 2 * ks, ahi, blo + 288, 16, 1);
                wg72<0, 0, 0>(acc, alo + 3 * ks, ahi, blo + 432, 16, 1);
                alo += 512;
            }
            wg_commit();
            wg_wait<1>();
            if (lead && (h | blk)) mb_arrive(prev);
            if (KIND == 1 && h == 2 && blk == 1 && T == 5 && lead) { mb_arrive_n(bb + XD(0), 2); mb_arrive_rem(rb + XD(0), 2); }
            prev = bar + 8;
        }
        slot += 3; if (slot == 12) { slot = 0; par ^= 1; }
    }
    wg_wait<0>();
#pragma unroll
    for (int i = 0; i < (KIND ? 36 : 72); i++) asm volatile("" : "+f"(acc[i]) :: "memory");
    if (lead) mb_arrive(prev);
}
template <int O> __device__ __forceinline__ void a_store(const float (&acc)[72], float* op, int q) {
#pragma unroll
    for (int i = 0; i < 4; i++) {
        *(float4*)(op + 16 * i) = make_float4(acc[O + 8 * i], acc[O + 8 * i + 1], acc[O + 8 * i + 4], acc[O + 8 * i + 5]);
        *(float4*)(op + 8 * 1152 + 16 * i) = make_float4(acc[O + 8 * i + 2], acc[O + 8 * i + 3], acc[O + 8 * i + 6], acc[O + 8 * i + 7]);
    }
    *(float2*)(op + 64 - 2 * q) = make_float2(acc[O + 32], acc[O + 33]);
    *(float2*)(op + 8 * 1152 + 64 - 2 * q) = make_float2(acc[O + 34], acc[O + 35]);
}

template <int PR> __device__ __forceinline__ void kv_red(const float (&kv)[72], float* base, int w, int g, int q) {
    if (w == 3) return;
#pragma unroll
    for (int r = 0; r < 2; r++) {
        const int R = 16 * w + g + 8 * r;
        int d = R - (PR ? 4 : 8) - 18 * (q >> 1);
        const bool one = R == (PR ? 40 : 0);
        const bool ok = one || (unsigned)d < 18u;
        if (one) d = 18;
        float* p = base + (2 * PR + (q >> 1)) * 720 + d * 4 + (q & 1) * 2;
        if (ok) {
#pragma unroll
            for (int j = 0; j < 9; j++)
                asm volatile("red.relaxed.gpu.global.add.v2.f32 [%0], {%1, %2};" :: "l"(p + j * 80), "f"(kv[36 * PR + 4 * j + 2 * r]), "f"(kv[36 * PR + 4 * j + 2 * r + 1]) : "memory");
        }
    }
}
__device__ __forceinline__ void kv_mma(float (&kv)[72], int g4) {
    wg_fence();
    const uint32_t alo = (((SB0 + A_AUX) >> 4) + g4 * 640) | (8u << 16), blo = ((SB0 + A_PHI) >> 4) | (8u << 16);
#pragma unroll
    for (int ks = 0; ks < 4; ks++) {
        wg72<1, 1, 0>(kv, alo + 16 * ks, 64, blo + 16 * ks, 64, ks);
        wg72<1, 1, 36>(kv, alo + 320 + 16 * ks, 64, blo + 580 + 16 * ks, 64, ks);
    }
    wg_commit();
}
__device__ __forceinline__ void o_write(const float (&acc)[72], uint32_t sb, uint32_t rsb, int part, int wg, int w, int lane) {
    mb_wait(sb + BAR + XD(part >> 1), 0);
    const uint32_t base = sb + A_X + part * 18432;
    const uint32_t a = base + ((lane >> 4) << 10) + (2 * w + ((lane >> 3) & 1)) * 128 + (lane & 7) * 16;
#pragma unroll
    for (int jp = 0; jp < 4; jp++) stsm4(a + jp * 2048, __float_as_uint(acc[36 + 4 * jp]), __float_as_uint(acc[37 + 4 * jp]), __float_as_uint(acc[38 + 4 * jp]), __float_as_uint(acc[39 + 4 * jp]));
    stsm2(a + 8192, __float_as_uint(acc[52]), __float_as_uint(acc[53]));
    proxy_fence();
    wg_bar(wg);
    if (w == 0) {
        bulk_s2s(rsb + A_X + part * 18432 + 9216, base, rsb + BAR + PART(2 * part + 1), 9216);
        e_arrive(sb + BAR + PART(2 * part), 1);
    }
}

__device__ __forceinline__ void a_consumer(const Params& P, uint32_t sb, int warp, int c, int tile) {
    const uint32_t bb = sb + BAR, rsb = sb ^ 0x1000000u, rb = rsb + BAR;
    const int wg = warp >> 2, w = warp & 3, lane = threadIdx.x & 31, g = lane >> 2, q = lane & 3, t = threadIdx.x & 127;
    const bool lead = lane == 0;
    asm volatile("bar.sync 14, 512;" ::: "memory");
    cl_arrive();
    PST(0);
    if (wg == 2) {
#pragma unroll 1
        for (int i = 0; i < 3; i++) {
            const int tt = t + 128 * i;
            if (tt < 324) {
                const int U = tile * 324 + tt, s = U / 288, rem = U - s * 288;
                int kb, col;
                const int half = (rem >> 2) & 1, qq = rem & 3;
                const int sl = rem / 72, ng = (rem - 72 * sl) >> 3;
                if (s < 18) { kb = 4 * s + (sl & 2) + half; col = 72 * (sl & 1); }
                else { const int t2 = s >= 27; kb = 8 * (s - 18 - 9 * t2) + 2 * sl + half; col = 144 + 72 * t2; }
                col += ng < 8 ? 16 * (ng >> 1) + 4 * qq + 2 * (ng & 1) : 64 + 2 * qq;
                const int part = kb / 18, r = kb - 18 * part, peer = r >= 9, jj = r - 9 * peer, own = c ^ peer;
                const int tq = part < 2 ? part ^ 1 : part, h0 = 16 * own + 4 * (tq ^ (2 * own));
                const uint32_t* src = P.wo + (18 * h0 + 2 * jj) * 288 + ((288 * c + col) >> 1);
                uint32_t v[8];
#pragma unroll
                for (int k = 0; k < 8; k++) v[k] = __ldg(src + ((k >> 1) * 18 + (k & 1)) * 288);
                uint4* dst = g_wimg + (size_t)(c * 108 + 72) * 576 + U * 2;
                dst[0] = make_uint4(__byte_perm(v[0], v[1], 0x5410), __byte_perm(v[2], v[3], 0x5410), __byte_perm(v[4], v[5], 0x5410), __byte_perm(v[6], v[7], 0x5410));
                dst[1] = make_uint4(__byte_perm(v[0], v[1], 0x7632), __byte_perm(v[2], v[3], 0x7632), __byte_perm(v[4], v[5], 0x7632), __byte_perm(v[6], v[7], 0x7632));
            }
        }
        proxy_fence_g(); __syncwarp();
        if (lead) mb_arrive(bb + SIG(0));
        const uint32_t e = get_epoch(bb);
        if (t < 90) g_kvacc[(e & 1) ^ 1][blockIdx.x * 90 + t] = make_float4(0.f, 0.f, 0.f, 0.f);
        cl_wait();
        PST(1);
    } else {
        cl_wait();
        const uint32_t la = sb + A_AUX + (2 * w + ((lane >> 3) & 1)) * 128 + (lane & 7) * 16 + 1024;
        const int jj = lane >> 4;
        if (wg == 0) {
            float acc[64];
            v_mainloop<128>(acc, bb, 0, lead);
            PST(1);
            mb_wait(bb + R1(6) + 8, 0);
#pragma unroll
            for (int jp = 0; jp < 8; jp++) {
                const int b = 2 * jp + 2 * c + jj;
                stsm4(la + (b + (b >= 9)) * 1024, pack2(acc[8 * jp], acc[8 * jp + 1]), pack2(acc[8 * jp + 2], acc[8 * jp + 3]), pack2(acc[8 * jp + 4], acc[8 * jp + 5]), pack2(acc[8 * jp + 6], acc[8 * jp + 7]));
            }
            proxy_fence(); __syncwarp();
            if (lead) mb_arrive(bb + VST(0));
        } else {
            float acc[80];
            v_mainloop<160>(acc, bb, 8192, lead);
            PST(1);
            uint32_t pk[40];
#pragma unroll
            for (int i = 0; i < 40; i++) pk[i] = pack2(acc[2 * i], acc[2 * i + 1]);
            mb_wait(bb + R1(6) + 8, 0);
            stsm4(la + (c ? jj : 17 + jj) * 1024, c ? pk[28] : pk[0], c ? pk[29] : pk[1], c ? pk[30] : pk[2], c ? pk[31] : pk[3]);
            sts128(sb + A_AUX + (t >> 6) * 10240 + (t & 63) * 16, 0x3f803f80u, 0x3f803f80u, 0x3f803f80u, 0x3f803f80u);
            if (t < 64) sts128(sb + A_AUX + 20480 + t * 16, 0x3f803f80u, 0x3f803f80u, 0x3f803f80u, 0x3f803f80u);
            proxy_fence(); __syncwarp();
            if (lead) mb_arrive(bb + VST(0));
            mb_wait(bb + KVD(0), 0);
#pragma unroll
            for (int jp = 0; jp < 10; jp++) {
                const int b = (c ? (jp < 7 ? 2 * jp + 4 : 2 * jp - 16) : 2 * jp - 2) + jj;
                if (jp != (c ? 7 : 0)) stsm4(la + (b + (b >= 9)) * 1024, pk[4 * jp], pk[4 * jp + 1], pk[4 * jp + 2], pk[4 * jp + 3]);
            }
            proxy_fence(); __syncwarp();
            if (lead) mb_arrive_n(bb + VST(1), 2);
        }
        PST(2);
    }
    const uint32_t par = get_epoch(bb) & 1;
    float acc[72];
    reg_def(acc);
    int T = wg == 2 ? 0 : wg + 1, gi = 0;
#pragma unroll 1
    for (;;) {
        const int pb = 3 + 7 * (T / 3);
        if (gi) {
#pragma unroll
            for (int i = 0; i < 36; i++) { acc[i] = acc[36 + i]; asm volatile("{ .reg .f32 t; mov.f32 %0, t; }" : "=f"(acc[36 + i])); }
        } else {
            if (T) mb_wait(bb + TOK(T - 1), 0);
            PST(pb);
            if (T < 2 || T == 6) { reg_def(acc); n_mainloop<0>(acc, bb, rb, T, lead); }
            else {
#pragma unroll
                for (int i = 0; i < 36; i++) asm volatile("{ .reg .f32 t; mov.f32 %0, t; }" : "=f"(acc[i]));
                n_mainloop<1>(acc, bb, rb, T, lead);
            }
            PST(pb + 1);
            if (T >= 6) break;
        }
        const int tq = T - 2;
        if (T >= 2) {
            if (T >= 4 && lead) { mb_arrive(bb + XD(1)); mb_arrive_rem(rb + XD(1), 1); }
            if (T == 5) o_write(acc, sb, rsb, 1, wg, w, lane);
            mb_wait(bb + KVR(tq), 0);
            const float4* ks = &g_kvacc[par][(16 * c + 4 * (tq ^ (2 * c)) + ((t >> 1) & 3)) * 180 + (t & 1) + 2 * (t >> 3)];
#pragma unroll
            for (int i = 0; i < 6; i++)
                asm volatile("ld.relaxed.gpu.global.v4.f32 {%0, %1, %2, %3}, [%4];" : "=f"(acc[36 + 4 * i]), "=f"(acc[37 + 4 * i]), "=f"(acc[38 + 4 * i]), "=f"(acc[39 + 4 * i])
                             : "l"(ks + (i < 5 || t < 80 ? 32 * i : 0)) : "memory");
            PST(pb + 2);
        }
        uint32_t p0[9], n0[9], p1[9], n1[9];
        softmax_row<0>(acc, p0, n0); softmax_row<2>(acc, p1, n1);
        if (T < 2) {
            PST(pb + 2 + 2 * gi);
            const uint32_t pa = sb + A_PHI + (q >> 1) * 9280 + 2 * w * 128 + g * 16 + (q & 1) * 8;
            mb_wait(bb + VST(T), 0);
            wg_bar(wg);
#pragma unroll
            for (int j = 0; j < 9; j++) { sts64(pa + j * 1024, p0[j], n0[j]); sts64(pa + j * 1024 + 128, p1[j], n1[j]); }
            proxy_fence(); wg_bar(wg);
            float kv[72];
            kv_mma(kv, gi);
            wg_wait<0>(); reg_fence(kv);
            if (gi && lead) mb_arrive(bb + KVD(T));
            float* kb = (float*)&g_kvacc[par][(16 * c + 8 * (T ^ c) + 4 * gi) * 180];
            kv_red<0>(kv, kb, w, g, q); kv_red<1>(kv, kb, w, g, q);
            __syncwarp();
            if (lead) mb_arrive(bb + SIG(1 + 2 * T + gi));
            PST(pb + 3 + 2 * gi);
            gi ^= 1;
            if (gi) continue;
        } else {
            PST(pb + 3);
            mb_wait(bb + (tq < 2 ? KVD(1) : NUMD(tq - 2)), 0);
            const uint32_t so = A_AUX + (tq & 1) * 23040;
            const int hq = (t >> 1) & 3;
#pragma unroll
            for (int i = 0; i < 6; i++) {
                const int cb = 16 * i + (t >> 3), b = (cb * 205) >> 11;
                if (i < 5 || t < 80) {
                    const uint32_t a = sb + so + cb * 128 + b * 1280 + (t & 7) * 16, vp = pack2(acc[36 + 4 * i], acc[37 + 4 * i]), vn = pack2(acc[38 + 4 * i], acc[39 + 4 * i]);
                    sts128(a, hq == 0 ? vp : 0, hq == 1 ? vp : 0, hq == 2 ? vp : 0, hq == 3 ? vp : 0);
                    sts128(a + 1280, hq == 0 ? vn : 0, hq == 1 ? vn : 0, hq == 2 ? vn : 0, hq == 3 ? vn : 0);
                }
            }
            proxy_fence(); wg_bar(wg);
            PST(pb + 4);
            float nm[40];
            wg_fence();
            const uint32_t blo = ((SB0 + so) >> 4) | (80u << 16);
#pragma unroll
            for (int b = 0; b < 9; b++) wgrs80(nm, p0[b], p1[b], n0[b], n1[b], blo + 160 * b, 8, b);
            wg_commit();
            wg_wait<0>(); reg_fence(nm);
            if (tq < 2 && lead) mb_arrive(bb + NUMD(tq));
            const float i0 = rcpf(nm[36] + 1e-6f), i1 = rcpf(nm[38] + 1e-6f);
#pragma unroll
            for (int j = 0; j < 9; j++) { acc[36 + 2 * j] = __uint_as_float(pack2(nm[4 * j] * i0, nm[4 * j + 1] * i0)); acc[37 + 2 * j] = __uint_as_float(pack2(nm[4 * j + 2] * i1, nm[4 * j + 3] * i1)); }
            PST(pb + 5);
            if (tq) o_write(acc, sb, rsb, tq == 1 ? 0 : tq, wg, w, lane);
            PST(pb + 6);
        }
        T += 3;
    }
    float* op = P.out + (size_t)(64 * tile + 16 * w + g) * 1152 + 288 * c + 4 * q + (wg == 2 ? 0 : 144 + 72 * wg);
    a_store<0>(acc, op, q);
    if (wg == 2) a_store<36>(acc, op + 72, q);
    PST(19);
}

__device__ __forceinline__ void b_producer(const Params& P, uint32_t sb, int pw, int c, int tile) {
    const uint32_t bb = sb + BAR;
    if (pw < 2) {
        int slot = pw + 1; uint32_t par = 1;
        const int w0 = c ? 40 : 0;
#pragma unroll 1
        for (int it = pw; it < 41; it += 2) {
            const uint32_t bar = bb + R1(slot), dst = sb + slot * 16384;
            int k0, k1, m0, m1;
            if (it < 18) { k0 = k1 = (it >> 1) * 64; m0 = w0 + 4 * pw; m1 = m0 + 8; }
            else if (it < 36) { const int b = it >= 27; k0 = k1 = (it - 18 - 9 * b) * 64; m0 = w0 + 16 + 8 * b; m1 = m0 + 4; }
            else { k0 = (it - 36) * 128; k1 = k0 + 64; m0 = m1 = c ? 36 : 32; }
            const bool wx = it < 18 && pw == 0;
            mb_wait(bar + 8, par);
            e_expect(bar, wx ? 16384 + 8192 : (it == 40 ? 8192 : 16384));
            if (wx) tma5(sb + B_X + it * 4096, &P.m[4], bar, k0, tile);
            tma4(dst, &P.m[5], bar, k0, m0);
            if (it != 40) tma4(dst + 8192, &P.m[5], bar, k1, m1);
            slot += 2; if (slot >= 7) { slot -= 7; par ^= 1; }
        }
        par = 1;
#pragma unroll 1
        for (int r = 0; r < 6; r++) {
#pragma unroll 1
            for (int s = pw; s < 10; s += 2) {
                const uint32_t bar = bb + R2(s);
                const int u = 5 * (r & 1) + (s >> 1), y = (pw ? 3 * c : 3 - 3 * c) + (r >> 1);
                if (r == 0) mb_wait(bb + R1((3 * s) >> 2) + 8, 1);
                mb_wait(r ? bar + 8 : bb + R1(min((3 * s + 2) >> 2, 6)) + 8, par);
                e_expect(bar, 12288);
                tma5(sb + s * 12288, &P.m[6 + 2 * (u & 1) + c], bar, u < 8 ? 32 * c + 64 * (u >> 1) : (c ? -32 : 256), 6 * y);
            }
            par ^= 1;
        }
    } else if (pw == 2) {
        read_epoch(bb);
    } else {
#pragma unroll
        for (int i = 0; i < 3; i++) e_expect(bb + RFULL(i), 24576);
        mb_wait_b(bb + EPO);
        mb_wait_b(bb + FSIG); signal_cnt(&g_cnt[(CNT_K + (tile >> 3)) * 32]); PSTP(1);
    }
}

__device__ __forceinline__ uint32_t LDX(const uint32_t* p) { uint32_t v;
    v = __ldg(p);
    return v; }
__device__ __forceinline__ void mma16(float (&d)[4], uint32_t a0, uint32_t a1, uint32_t a2, uint32_t a3, uint32_t b0, uint32_t b1) {
    asm("mma.sync.aligned.m16n8k16.row.col.f32.bf16.bf16.f32 {%0,%1,%2,%3}, {%4,%5,%6,%7}, {%8,%9}, {%0,%1,%2,%3};"
        : "+f"(d[0]), "+f"(d[1]), "+f"(d[2]), "+f"(d[3]) : "r"(a0), "r"(a1), "r"(a2), "r"(a3), "r"(b0), "r"(b1));
}
__device__ __forceinline__ void mma8(float (&d)[4], uint32_t a0, uint32_t a1, uint32_t b0) {
    asm("mma.sync.aligned.m16n8k8.row.col.f32.bf16.bf16.f32 {%0,%1,%2,%3}, {%4,%5}, {%6}, {%0,%1,%2,%3};"
        : "+f"(d[0]), "+f"(d[1]), "+f"(d[2]), "+f"(d[3]) : "r"(a0), "r"(a1), "r"(b0));
}

struct ScanC { cf l, l16, l32, l64, m16, m512; float ka, kb, kc, kd; };
__device__ __forceinline__ void scan_consts(ScanC& s, float lr, float li, float kr, float ki, int src, int q, int swap) {
    lr = __shfl_sync(0xffffffffu, lr, src, 4); li = __shfl_sync(0xffffffffu, li, src, 4); kr = __shfl_sync(0xffffffffu, kr, src, 4); ki = __shfl_sync(0xffffffffu, ki, src, 4);
    s.l = {lr, swap ? -li : li};
    s.l16 = csq(csq(csq(csq(s.l)))); s.l32 = csq(s.l16); s.l64 = csq(s.l32);
    const cf l512 = csq(csq(csq(s.l64))), l1024 = csq(l512), one = {1.f, 0.f};
    s.m16 = cmul(csel(q & 1, s.l16, one), csel(q & 2, s.l32, one));
    s.m512 = cmul(csel(q & 1, l512, one), csel(q & 2, l1024, one));
    s.ka = swap ? -ki : kr; s.kb = swap ? kr : -ki; s.kc = swap ? -kr : -ki; s.kd = swap ? -ki : -kr;
}
__device__ __forceinline__ void agg_st(u64* p, cf v) {
    uint32_t a = __float_as_uint(v.x);
    if (a == 0) a = 0x80000000u;
    asm volatile("{ .reg .b64 t; mov.b64 t, {%1, %2}; st.relaxed.gpu.global.b64 [%0], t; }" :: "l"(p), "r"(a), "r"(__float_as_uint(v.y)) : "memory");
}
template <int I> __device__ __forceinline__ void agg_ld(cf& v, const u64* p, int np) {
    asm volatile("{ .reg .pred p; .reg .b64 t; mov.b64 t, {%0, %1}; setp.gt.s32 p, %3, %4; @p ld.relaxed.gpu.global.b64 t, [%2]; mov.b64 {%0, %1}, t; }" : "+f"(v.x), "+f"(v.y) : "l"(p), "r"(np), "n"(I) : "memory");
}
template <int O> __device__ __forceinline__ cf scan_pass1(float (&a)[64], const ScanC& s, int q, cf& excl) {
    cf h = {a[O], a[O + 2]};
#pragma unroll
    for (int i = 1; i < 16; i++) h = cfma(s.l, h, {a[O + 4 * (i >> 1) + (i & 1)], a[O + 4 * (i >> 1) + 2 + (i & 1)]});
    cf y = {__shfl_up_sync(0xffffffffu, h.x, 1, 4), __shfl_up_sync(0xffffffffu, h.y, 1, 4)};
    if (q >= 1) h = cfma(s.l16, y, h);
    y = {__shfl_up_sync(0xffffffffu, h.x, 2, 4), __shfl_up_sync(0xffffffffu, h.y, 2, 4)};
    if (q >= 2) h = cfma(s.l32, y, h);
    y = {__shfl_up_sync(0xffffffffu, h.x, 1, 4), __shfl_up_sync(0xffffffffu, h.y, 1, 4)};
    excl = csel(q >= 1, y, {0.f, 0.f});
    return h;
}
template <int O> __device__ __forceinline__ void scan_scale(const float (&a)[64], float (&b)[64], const ScanC& s) {
#pragma unroll
    for (int i = 0; i < 16; i++) {
        const int ip = O + 4 * (i >> 1) + (i & 1);
        asm volatile("{ .reg .f32 a, b; mul.f32 a, %5, %3; mul.f32 b, %7, %3; fma.rn.f32 %1, %6, %2, b; fma.rn.f32 %0, %4, %2, a; }"
                     : "=f"(b[ip]), "=f"(b[ip + 2]) : "f"(a[ip]), "f"(a[ip + 2]), "f"(s.ka), "f"(s.kb), "f"(s.kc), "f"(s.kd));
    }
}
template <int O> __device__ __forceinline__ void scan_pass2(float (&a)[64], const ScanC& s, const cf (&v)[8], cf excl, int swap, uint32_t (&re)[8], uint32_t (&im)[8]) {
    cf cr = v[7];
#pragma unroll
    for (int i = 6; i >= 0; i--) cr = cfma(s.l64, cr, v[i]);
    cr = cmul(cr, s.m512);
    cr.x += __shfl_xor_sync(0xffffffffu, cr.x, 1); cr.y += __shfl_xor_sync(0xffffffffu, cr.y, 1);
    cr.x += __shfl_xor_sync(0xffffffffu, cr.x, 2); cr.y += __shfl_xor_sync(0xffffffffu, cr.y, 2);
    cr = cfma(s.m16, cr, excl);
    cf h = {fmaf(s.ka, cr.x, s.kb * cr.y), fmaf(s.kc, cr.x, s.kd * cr.y)};
    const cf lc = {s.l.x, swap ? s.l.y : -s.l.y};
#pragma unroll
    for (int j = 0; j < 8; j++) {
        const cf h0 = cfma(lc, h, {a[O + 4 * j], a[O + 4 * j + 2]});
        h = cfma(lc, h0, {a[O + 4 * j + 1], a[O + 4 * j + 3]});
        re[j] = pack2(h0.x, h.x); im[j] = pack2(h0.y, h.y);
    }
}
__device__ __forceinline__ void b_init_xd(float (&a)[48], const Params& P, int row, int col) {
    const uint2* xp = P.xb + row * 144 + (col >> 2); const uint2* dp = P.dsk + (col >> 2);
#pragma unroll
    for (int i = 0; i < 6; i++) {
        const uint2 d = __ldg(dp + 4 * i);
#pragma unroll
        for (int r = 0; r < 2; r++) {
            const uint2 x = __ldg(xp + r * 8 * 144 + 4 * i);
            uint32_t u0, u1;
            asm("mul.rn.bf16x2 %0, %1, %2;" : "=r"(u0) : "r"(x.x), "r"(d.x)); asm("mul.rn.bf16x2 %0, %1, %2;" : "=r"(u1) : "r"(x.y), "r"(d.y));
            a[8 * i + 2 * r] = __uint_as_float(u0 << 16); a[8 * i + 2 * r + 1] = __uint_as_float(u0 & 0xffff0000u);
            a[8 * i + 4 + 2 * r] = __uint_as_float(u1 << 16); a[8 * i + 5 + 2 * r] = __uint_as_float(u1 & 0xffff0000u);
        }
    }
}
__device__ __forceinline__ void b_send(const float (&a)[48], uint32_t bb, uint32_t rsb, int i3, int t) {
    mb_wait(bb + RFREE(i3), 0);
    const uint32_t dst = rsb + B_RECV + t * 16, bar = rsb + BAR + RFULL(i3);
#pragma unroll
    for (int i = 0; i < 12; i++) {
        asm volatile("st.async.weak.shared::cluster.mbarrier::complete_tx::bytes.v4.f32 [%0], {%1, %2, %3, %4}, [%5];"
            :: "r"(dst + i * 2048), "f"(a[4 * i]), "f"(a[4 * i + 1]), "f"(a[4 * i + 2]), "f"(a[4 * i + 3]), "r"(bar) : "memory");
    }
}
template <int FULL> __device__ __forceinline__ void b2_stage(float (&acc)[48], uint32_t alo, uint32_t blo, uint32_t first) {
    wg_fence();
    wg96<1, 0, 0>(acc, alo, DHI_SW, blo, DHI_SW, first);
    wg96<1, 0, 0>(acc, alo + 128, DHI_SW, blo + 2, DHI_SW, 1);
    if (FULL) { wg96<1, 0, 0>(acc, alo + 256, DHI_SW, blo + 4, DHI_SW, 1); wg96<1, 0, 0>(acc, alo + 384, DHI_SW, blo + 6, DHI_SW, 1); }
    wg_commit();
    wg_wait<1>();
}
template <int FULL> __device__ __forceinline__ void b2_dual(float (&as)[48], float (&acc)[48], uint32_t bb, int u, int r, uint32_t alo, uint32_t ko, uint32_t& prev, bool lead) {
    const int s = u < 5 ? 2 * u : 2 * u - 10;
    const uint32_t bar = bb + R2(s), blo = (SB0 >> 4) + s * 768 + ko, par = u >= 5;
    if (!(u & 1)) mb_wait(bb + HR(u >> 1), 0);
    mb_wait(bar, par);
    b2_stage<FULL>(as, alo, blo, u);
    if (lead && u) mb_arrive(prev);
    mb_wait(bar + 16, par);
    if (!FULL && u == 9 && lead) mb_arrive(bb + TOK(3 + r));
    b2_stage<FULL>(acc, alo, blo + 768, 1);
    if (lead) mb_arrive(bar + 8);
    prev = bar + 24;
}

__device__ __forceinline__ void b_consumer(const Params& P, uint32_t sb, int warp, int c, int tile) {
    const uint32_t bb = sb + BAR, rsb = sb ^ 0x1000000u, rb = rsb + BAR;
    const int wg = warp >> 2, w = warp & 3, lane = threadIdx.x & 31, g = lane >> 2, q = lane & 3, t = threadIdx.x & 127;
    const bool lead = lane == 0;
    const int swap = P.swap;
    const int mq = wg == 0 ? (q < 2 ? q : q + 4) : (wg == 1 ? (q < 2 ? q + 2 : 8) : 4 + (q & 1));
    const int sq = (c ? (mq < 8 ? 320 + 32 * mq : 288) : 32 * mq) + 8 * w + g;
    const unsigned short hre = __ldg(P.lre + sq), him = __ldg(P.lim + sq), hdt = __ldg(P.ldt + sq);
    {
        const int kb0 = 36 * c + 3 * warp;
        const uint32_t* src = P.wqkv + (8 * kb0 + g) * 864 + 9 * tile + q;
        uint32_t b[2][3][3];
#pragma unroll
        for (int mtx = 0; mtx < 2; mtx++)
#pragma unroll
            for (int nt = 0; nt < 3; nt++) {
                const uint32_t* s = src + nt * 8 * 864 + (mtx ? 0 : 288);
                b[mtx][nt][0] = LDX(s); b[mtx][nt][1] = LDX(s + 4); b[mtx][nt][2] = q == 0 ? LDX(s + 8) : 0u;
            }
        const unsigned short* wp = P.wphi + tile * 324 + g;
        const unsigned short* wq = wp + 36 * q;
        const int fo = 16 + (g & 1) - g;
        unsigned short h[18];
#pragma unroll
        for (int i = 0; i < 2; i++) {
            h[i] = __ldg(wq + 18 * i); h[2 + i] = __ldg(wq + 18 * i + 8); h[4 + i] = __ldg(wq + 18 * i + 144); h[6 + i] = __ldg(wq + 18 * i + 152);
            h[8 + i] = __ldg(wp + 18 * i + 288); h[10 + i] = __ldg(wp + 18 * i + 296);
            h[12 + i] = __ldg(wq + 18 * i + fo); h[14 + i] = __ldg(wq + 18 * i + 144 + fo); h[16 + i] = __ldg(wp + 18 * i + 288 + fo);
        }
        asm volatile("bar.sync 14, 512;" ::: "memory");
        cl_arrive();
        PST(0);
        uint32_t a[4], a8[2], e0, e2, e8;
#define WP(i) ((uint32_t)h[2 * (i)] | ((uint32_t)h[2 * (i) + 1] << 16))
        a[0] = WP(0); a[1] = WP(1); a[2] = WP(2); a[3] = WP(3); a8[0] = WP(4); a8[1] = WP(5); e0 = WP(6); e2 = WP(7); e8 = WP(8);
#undef WP
        PST(16);
        const int cc = tile >> 4, G = (tile >> 2) & 3, tq = G ^ (2 * cc);
        uint8_t* img = (uint8_t*)g_wimg + (size_t)cc * 108 * 9216 + (g >> 1) * 256 + (2 * (tile & 3) + (g & 1)) * 16 + 4 * q;
#pragma unroll
        for (int mtx = 0; mtx < 2; mtx++)
#pragma unroll
            for (int nt = 0; nt < 3; nt++) {
                float d0[4] = {0.f, 0.f, 0.f, 0.f}, d1[4] = {0.f, 0.f, 0.f, 0.f};
                mma16(d0, a[0], a[1], a[2], a[3], b[mtx][nt][0], b[mtx][nt][1]); mma8(d0, a8[0], a8[1], b[mtx][nt][2]);
                mma16(d1, e0, 0u, e2, 0u, b[mtx][nt][0], b[mtx][nt][1]); mma8(d1, e8, 0u, b[mtx][nt][2]);
                const float L2E = 1.4426950408889634f;
                const int kb = kb0 + nt;
                uint8_t* d = img + (kb & 1) * 128 + (mtx ? (36 + 9 * tq) * 9216 + (kb >> 1) * 2304 : 18 * (tq >> 1) * 9216 + (G & 1) * 2304 + (kb >> 1) * 4608);
                *(uint32_t*)d = pack2(d0[0] * L2E, d0[1] * L2E);
                *(uint32_t*)(d + 1024) = pack2(d0[2] * L2E, d0[3] * L2E);
                if (g < 2) *(uint32_t*)(d + 2048) = pack2(d1[0] * L2E, d1[1] * L2E);
            }
        PST(19);
        proxy_fence_g(); __syncwarp();
        if (lead) mb_arrive(bb + FSIG);
    }
    PST(15);
    float lr, li, kr, ki;
    {
        const float a = bf2f(hre), b = bf2f(him), dt = __bfloat162float(__float2bfloat16(expf(bf2f(hdt))));
        const float e = expf(dt * a); float sn, cs;
        sincospif(dt * b * 0.31830988618379067f, &sn, &cs);
        lr = e * cs; li = e * sn;
        const float id = __fdividef(2.f, fmaf(a, a, b * b)), nr = lr - 1.f;
        kr = fmaf(nr, a, li * b) * id; ki = fmaf(li, a, -nr * b) * id;
    }
    const uint32_t ep = get_epoch(bb) & 1;
    if (wg == 2) { ((uint4*)g_agg[ep ^ 1])[(2 * tile + c) * 144 + t] = make_uint4(0, 0, 0, 0); if (t < 16) ((uint4*)g_agg[ep ^ 1])[(2 * tile + c) * 144 + 128 + t] = make_uint4(0, 0, 0, 0); }
    cl_wait();
    PST(1);
    int task = wg;
#pragma unroll 1
    for (;;) {
        float acc[64];
        reg_def(acc);
        const uint32_t xlo = (SB0 + B_X) >> 4;
        uint32_t prev = 0;
        if (task < 2) {
            int slot = 1; uint32_t par = 0;
#pragma unroll 1
            for (int kc = 0; kc < 9; kc++) {
#pragma unroll
                for (int h = 0; h < 2; h++) {
                    const uint32_t bar = bb + R1(slot), alo = (SB0 >> 4) + slot * 1024 + task * 512, blo = xlo + kc * 512;
                    mb_wait(bar, par);
                    if (h == 1 && kc == 8 && task == 0 && lead) mb_arrive(bb + TOK(0));
                    wg_fence();
#pragma unroll
                    for (int ks = 0; ks < 4; ks++) { if (h) wg64<0, 0, 32>(acc, alo + 2 * ks, DHI_SW, blo + 2 * ks, DHI_SW, ks | kc); else wg64<0, 0, 0>(acc, alo + 2 * ks, DHI_SW, blo + 2 * ks, DHI_SW, ks | kc); }
                    wg_commit();
                    wg_wait<1>();
                    if (lead && (h | kc)) mb_arrive(prev);
                    prev = bar + 8;
                    if (++slot == 7) { slot = 0; par ^= 1; }
                }
            }
            wg_wait<0>(); reg_fence(acc);
            if (lead) mb_arrive(prev);
        } else if (task < 4) {
            mb_wait(bb + TOK(task - 2), 0);
            PST(6);
            int slot = task == 2 ? 5 : 0; uint32_t par = 0;
#pragma unroll 1
            for (int kc = 0; kc < 9; kc++) {
                const uint32_t bar = bb + R1(slot), alo = (SB0 >> 4) + slot * 1024, blo = xlo + kc * 512;
                mb_wait(bar, par);
                if (kc == 8 && lead) mb_arrive(bb + TOK(task - 1));
                wg_fence();
#pragma unroll
                for (int ks = 0; ks < 4; ks++) { wg64<0, 0, 0>(acc, alo + 2 * ks, DHI_SW, blo + 2 * ks, DHI_SW, ks | kc); wg64<0, 0, 32>(acc, alo + 512 + 2 * ks, DHI_SW, blo + 2 * ks, DHI_SW, ks | kc); }
                wg_commit();
                wg_wait<1>();
                if (lead && kc) mb_arrive_n(prev, 2);
                prev = bar + 8;
                if (++slot == 7) { slot = 0; par ^= 1; }
            }
            wg_wait<0>(); reg_fence(acc);
            if (lead) { mb_arrive_n(prev, 2); if (task == 3) mb_arrive_rem(rb + RFREE(0), 1); }
        } else {
            mb_wait(bb + TOK(2), 0);
            PST(6);
#pragma unroll 1
            for (int st = 0; st < 4; st++) {
                const uint32_t bar = bb + R1(2 + st), alo = (SB0 >> 4) + (2 + st) * 1024, blo = xlo + st * 1024;
                mb_wait(bar, 1);
                wg_fence();
#pragma unroll
                for (int ks = 0; ks < 8; ks++) wg64<0, 0, 0>(acc, alo + 2 * (ks & 3) + 512 * (ks >> 2), DHI_SW, blo + 2 * (ks & 3) + 512 * (ks >> 2), DHI_SW, ks | st);
                wg_commit();
                wg_wait<1>();
                if (lead && st) { mb_arrive_n(prev, 2); if (st & 1) mb_arrive(bb + BXD(st >> 1)); }
                prev = bar + 8;
            }
            mb_wait(bb + R1(6), 1);
            wg_fence();
#pragma unroll
            for (int ks = 0; ks < 4; ks++) wg64<0, 0, 0>(acc, (SB0 >> 4) + 6 * 1024 + 2 * ks, DHI_SW, xlo + 4096 + 2 * ks, DHI_SW, 1);
            wg_commit();
            wg_wait<1>();
            if (lead) mb_arrive_n(prev, 2);
            prev = bb + R1(6) + 8;
            wg_wait<0>(); reg_fence(acc);
            if (lead) { mb_arrive_n(prev, 2); mb_arrive_rem(rb + RFREE(0), 1); }
        }
        PST(task < 3 ? 2 : 7);
        const bool two = task < 4;
        const int st0 = (c ? (two ? 320 + 64 * task : 288) : 64 * task) + 8 * w + g;
        ScanC s0, s1;
        scan_consts(s0, lr, li, kr, ki, task < 3 ? 0 : 2, q, swap);
        scan_consts(s1, lr, li, kr, ki, task < 3 ? 1 : 3, q, swap);
        cf x0, x1;
        const cf t0 = scan_pass1<0>(acc, s0, q, x0), t1 = scan_pass1<32>(acc, s1, q, x1);
        u64* ag = g_agg[ep] + tile * 576 + st0;
        if (q == 3) { agg_st(ag, t0); if (two) agg_st(ag + 32, t1); }
        float us[64];
        scan_scale<0>(acc, us, s0); scan_scale<32>(acc, us, s1);
        PST(task < 3 ? 3 : 8);
        cf v0[8], v1[8];
        {
            const int np = tile - 8 * q, np1 = two ? np : 0;
            const u64* pg = ag - (8 * q + 1) * 576;
#pragma unroll
            for (int i = 0; i < 8; i++) v0[i] = v1[i] = {-0.f, 0.f};
            for (;;) {
                agg_ld<0>(v0[0], pg, np); agg_ld<1>(v0[1], pg - 576, np); agg_ld<2>(v0[2], pg - 2 * 576, np); agg_ld<3>(v0[3], pg - 3 * 576, np);
                agg_ld<4>(v0[4], pg - 4 * 576, np); agg_ld<5>(v0[5], pg - 5 * 576, np); agg_ld<6>(v0[6], pg - 6 * 576, np); agg_ld<7>(v0[7], pg - 7 * 576, np);
                agg_ld<0>(v1[0], pg + 32, np1); agg_ld<1>(v1[1], pg + 32 - 576, np1); agg_ld<2>(v1[2], pg + 32 - 2 * 576, np1); agg_ld<3>(v1[3], pg + 32 - 3 * 576, np1);
                agg_ld<4>(v1[4], pg + 32 - 4 * 576, np1); agg_ld<5>(v1[5], pg + 32 - 5 * 576, np1); agg_ld<6>(v1[6], pg + 32 - 6 * 576, np1); agg_ld<7>(v1[7], pg + 32 - 7 * 576, np1);
                bool ok = true;
#pragma unroll
                for (int i = 0; i < 8; i++) ok = ok && __float_as_uint(v0[i].x) != 0 && __float_as_uint(v1[i].x) != 0;
                if (__all_sync(0xffffffffu, ok)) break;
            }
        }
        PST(task < 3 ? 4 : 9);
        uint32_t re0[8], im0[8], re1[8], im1[8];
        scan_pass2<0>(us, s0, v0, x0, swap, re0, im0); scan_pass2<32>(us, s1, v1, x1, swap, re1, im1);
        if (task >= 2) mb_wait(bb + BXD(task >= 3), 0);
        const uint32_t ha = sb + B_HD + task * 16384 + (8 * w + g) * 128, h0 = ha + ((2 * q) ^ g) * 16, h1 = ha + ((2 * q + 1) ^ g) * 16, io = two ? 8192 : 4096;
        sts128(h0, re0[0], re0[1], re0[2], re0[3]); sts128(h1, re0[4], re0[5], re0[6], re0[7]);
        sts128(h0 + io, im0[0], im0[1], im0[2], im0[3]); sts128(h1 + io, im0[4], im0[5], im0[6], im0[7]);
        if (two) {
            sts128(h0 + 4096, re1[0], re1[1], re1[2], re1[3]); sts128(h1 + 4096, re1[4], re1[5], re1[6], re1[7]);
            sts128(h0 + 12288, im1[0], im1[1], im1[2], im1[3]); sts128(h1 + 12288, im1[4], im1[5], im1[6], im1[7]);
        }
        proxy_fence(); __syncwarp();
        if (lead) mb_arrive(bb + HR(task));
        PST(task < 3 ? 5 : 10);
        if (task >= 2) break;
        task += 3;
    }
    const int row = 64 * tile + 16 * w + g;
    const uint32_t hlo = (SB0 + B_HD) >> 4, ko = 4 * c;
    const int r = wg == 2 ? 0 : 1 + wg, col = 288 * c + 96 * r + 4 * q;
    float acc[48], as[48];
    b_init_xd(acc, P, row, col);
    reg_def(as);
    uint32_t prev = 0;
    if (r) mb_wait(bb + TOK(2 + r), 0);
    PST(11);
#pragma unroll 1
    for (int u = 0; u < 8; u++) b2_dual<1>(as, acc, bb, u, r, hlo + u * 512, 0, prev, lead);
#pragma unroll 1
    for (int u = 8; u < 10; u++) b2_dual<0>(as, acc, bb, u, r, hlo + 2048 + u * 256, ko, prev, lead);
    wg_wait<0>(); reg_fence(as); reg_fence(acc);
    if (lead) mb_arrive(prev);
    PST(12);
    b_send(as, bb, rsb, r, t);
    mb_wait_cl(bb + RFULL(r), 0);
    PST(13);
    float* op = P.out + (size_t)row * 1152 + 576 + col;
#pragma unroll
    for (int i = 0; i < 12; i++) asm volatile("ld.shared.v4.f32 {%0, %1, %2, %3}, [%4];" : "=f"(as[4 * i]), "=f"(as[4 * i + 1]), "=f"(as[4 * i + 2]), "=f"(as[4 * i + 3]) : "r"(sb + B_RECV + t * 16 + i * 2048) : "memory");
    __syncwarp();
    if (r < 2 && lead) mb_arrive_rem(rb + RFREE(r + 1), 2);
#pragma unroll
    for (int i = 0; i < 12; i++) {
        const int o = 8 * (i >> 1) + 2 * (i & 1);
        *(float4*)(op + (i & 1) * 8 * 1152 + 16 * (i >> 1)) = make_float4(acc[o] + as[o], acc[o + 1] + as[o + 1], acc[o + 4] + as[o + 4], acc[o + 5] + as[o + 5]);
    }
    PST(14);
}

__global__ void __launch_bounds__(512, 1) fused_kernel(const __grid_constant__ Params P) {
    extern __shared__ __align__(1024) uint8_t smem_raw[];
    uint32_t sb = (uint32_t)__cvta_generic_to_shared(smem_raw);
    asm volatile("mov.b32 %0, %0;" : "+r"(sb));
    const int warp = __shfl_sync(0xffffffffu, threadIdx.x >> 5, 0);
    const int c = blockIdx.x & 1, isb = blockIdx.x >> 6, tile = (blockIdx.x >> 1) & 31;
    const uint32_t bb = sb + BAR;
    if (warp >= 12) {
        asm volatile("setmaxnreg.dec.sync.aligned.u32 32;");
        if (elect_one()) {
            if (warp == 12) {
#pragma unroll
                for (int i = 0; i < 7; i++) { mb_init(bb + R1(i), 1); mb_init(bb + R1(i) + 8, 8); }
                mb_arrive(bb + R1(0)); mb_arrive_n(bb + R1(0) + 8, 8);
                if (!isb) { mb_arrive(bb + R1(1)); mb_arrive_n(bb + R1(1) + 8, 8); mb_arrive(bb + R1(2)); mb_arrive_n(bb + R1(2) + 8, 8); }
            } else if (warp == 13) {
                asm volatile("prefetch.tensormap [%0];" :: "l"(&P.m[4 * isb]) : "memory");
                asm volatile("prefetch.tensormap [%0];" :: "l"(&P.m[1 + 4 * isb]) : "memory");
                asm volatile("prefetch.tensormap [%0];" :: "l"(&P.m[2 + 4 * isb + c]) : "memory");
                asm volatile("prefetch.tensormap [%0];" :: "l"(&P.m[8 * isb + c]) : "memory");
#pragma unroll
                for (int i = 64; i < 79; i++) mb_init(bb + 8 * i, 1);
            } else if (warp == 14) {
#pragma unroll
                for (int i = 40; i < 60; i++) mb_init(bb + 8 * i, 4);
#pragma unroll
                for (int i = 80; i < 87; i++) mb_init(bb + 8 * i, i < 83 ? 8 : (i < 85 ? 16 : (i < 86 ? 15 : 12)));
            } else {
                if (sb != (SB0 | ((uint32_t)c << 24))) asm volatile("trap;");
#pragma unroll
                for (int i = 0; i < 12; i++) { mb_init(bb + R2(i), 1); mb_init(bb + R2(i) + 8, 4); }
            }
            asm volatile("fence.mbarrier_init.release.cluster;" ::: "memory");
        }
        __syncwarp();
        asm volatile("bar.arrive 14, 512;" ::: "memory");
        asm volatile("bar.sync 15, 128;" ::: "memory");
        cl_arrive();
        if (isb) b_producer(P, sb, warp - 12, c, tile); else a_producer(P, sb, warp - 12, c, tile);
        if (warp == 15) mb_wait_b(bb + DONE); else e_arrive(bb + DONE, 1);
        cl_wait();
        cl_arrive(); cl_wait();
    } else {
        asm volatile("setmaxnreg.inc.sync.aligned.u32 160;");
        if (isb) b_consumer(P, sb, warp, c, tile); else a_consumer(P, sb, warp, c, tile);
        __syncwarp();
        e_arrive(bb + DONE, 1);
        cl_arrive(); cl_wait();
    }
}

typedef CUresult (*EncodeTiledFn)(CUtensorMap*, CUtensorMapDataType, cuuint32_t, void*, const cuuint64_t*, const cuuint64_t*, const cuuint32_t*, const cuuint32_t*,
                                  CUtensorMapInterleave, CUtensorMapSwizzle, CUtensorMapL2promotion, CUtensorMapFloatOOBfill);

extern "C" void kernel_launch(void* const* d_in, const int* in_sizes, int n_in, void* d_out, int out_size) {
    static EncodeTiledFn enc = nullptr;
    if (!enc) {
        void* fn = nullptr; cudaDriverEntryPointQueryResult qr;
        cudaGetDriverEntryPoint("cuTensorMapEncodeTiled", &fn, cudaEnableDefault, &qr);
        enc = (EncodeTiledFn)fn;
        cudaFuncSetAttribute(fused_kernel, cudaFuncAttributeMaxDynamicSharedMemorySize, 232448);
    }
    Params P;
    const cuuint32_t es[5] = {1, 1, 1, 1, 1};
    auto mk = [&](int i, void* base, int rank, const cuuint64_t* gd, const cuuint64_t* gs, const cuuint32_t* bd) {
        enc(&P.m[i], CU_TENSOR_MAP_DATA_TYPE_BFLOAT16, rank, base, gd, gs, bd, es, CU_TENSOR_MAP_INTERLEAVE_NONE, CU_TENSOR_MAP_SWIZZLE_128B,
            CU_TENSOR_MAP_L2_PROMOTION_L2_128B, CU_TENSOR_MAP_FLOAT_OOB_FILL_NONE);
    };
    { const cuuint64_t gd[2] = {576, 2048}, gs[1] = {1152}; const cuuint32_t bd[2] = {64, 64}; mk(0, d_in[0], 2, gd, gs, bd); }
    { const cuuint64_t gd[3] = {64, 576, 27}, gs[2] = {3456, 128}; const cuuint32_t bd[3] = {64, 32, 2}; mk(1, d_in[1], 3, gd, gs, bd); }
    for (int c = 0; c < 2; c++) { const cuuint64_t gd[2] = {(cuuint64_t)(c ? 1472 : 1440), 576}, gs[1] = {3456}; const cuuint32_t bd[2] = {64, 32}; mk(2 + c, d_in[1], 2, gd, gs, bd); }
    { const cuuint64_t gd[5] = {576, 2, 4, 8, 32}, gs[4] = {1152, 16 * 1152, 2 * 1152, 64 * 1152}; const cuuint32_t bd[5] = {64, 2, 4, 8, 1}; mk(4, d_in[4], 5, gd, gs, bd); }
    const uintptr_t bre = (uintptr_t)d_in[7], bim = (uintptr_t)d_in[8];
    P.swap = bim < bre;
    { const cuuint64_t gd[4] = {576, 8, 2, 72}, gs[3] = {1152, (cuuint64_t)(P.swap ? bre - bim : bim - bre), 8 * 1152}; const cuuint32_t bd[4] = {64, 8, 2, 4};
      mk(5, P.swap ? d_in[8] : d_in[7], 4, gd, gs, bd); }
    for (int im = 0; im < 2; im++) for (int c = 0; c < 2; c++) {
        const cuuint64_t gd[5] = {288, 2, 4, 2, 36}, gs[4] = {1152, 4 * 1152, 2 * 1152, 16 * 1152}; const cuuint32_t bd[5] = {64, 2, 4, 2, 6};
        mk(6 + 2 * im + c, (uint8_t*)d_in[9 + im] + 576 * c, 5, gd, gs, bd);
    }
    P.wqkv = (const uint32_t*)d_in[1]; P.wphi = (const unsigned short*)d_in[2]; P.wo = (const uint32_t*)d_in[3];
    P.xb = (const uint2*)d_in[4]; P.lre = (const unsigned short*)d_in[5]; P.lim = (const unsigned short*)d_in[6]; P.ldt = (const unsigned short*)d_in[11]; P.dsk = (const uint2*)d_in[12];
    P.out = (float*)d_out;
    cudaLaunchConfig_t cfg = {};
    cfg.gridDim = dim3(128); cfg.blockDim = dim3(512); cfg.dynamicSmemBytes = 232448; cfg.stream = cudaStreamPerThread;
    cudaLaunchAttribute at[1];
    at[0].id = cudaLaunchAttributeClusterDimension; at[0].val.clusterDim.x = 2; at[0].val.clusterDim.y = 1; at[0].val.clusterDim.z = 1;
    cfg.attrs = at; cfg.numAttrs = 1;
    cudaLaunchKernelEx(&cfg, fused_kernel, P);
}
```

```cpp
#include <cuda_runtime.h>
#include <cuda.h>
#include <cuda_bf16.h>
#include <stdint.h>

typedef unsigned long long u64;
template <int TA, int TB, int O, int L> __device__ __forceinline__ void wg72(float (&d)[L], uint32_t alo, uint32_t ahi, uint32_t blo, uint32_t bhi, uint32_t acc) {
    asm volatile("{ .reg .pred p; .reg .b64 da, db; setp.ne.u32 p, %40, 0; mov.b64 da, {%36, %37}; mov.b64 db, {%38, %39};\n"
        "wgmma.mma_async.sync.aligned.m64n72k16.f32.bf16.bf16 {%0, %1, %2, %3, %4, %5, %6, %7, %8, %9, %10, %11, %12, %13, %14, %15, %16, %17, %18, %19, %20, %21, %22, %23, %24, %25, %26, %27, %28, %29, %30, %31, %32, %33, %34, %35}, da, db, p, 1, 1, %41, %42; }"
        : "+f"(d[O + 0]), "+f"(d[O + 1]), "+f"(d[O + 2]), "+f"(d[O + 3]), "+f"(d[O + 4]), "+f"(d[O + 5]), "+f"(d[O + 6]), "+f"(d[O + 7]), "+f"(d[O + 8]), "+f"(d[O + 9]), "+f"(d[O + 10]), "+f"(d[O + 11]), "+f"(d[O + 12]), "+f"(d[O + 13]), "+f"(d[O + 14]), "+f"(d[O + 15]), "+f"(d[O + 16]), "+f"(d[O + 17]), "+f"(d[O + 18]), "+f"(d[O + 19]), "+f"(d[O + 20]), "+f"(d[O + 21]), "+f"(d[O + 22]), "+f"(d[O + 23]), "+f"(d[O + 24]), "+f"(d[O + 25]), "+f"(d[O + 26]), "+f"(d[O + 27]), "+f"(d[O + 28]), "+f"(d[O + 29]), "+f"(d[O + 30]), "+f"(d[O + 31]), "+f"(d[O + 32]), "+f"(d[O + 33]), "+f"(d[O + 34]), "+f"(d[O + 35]) : "r"(alo), "r"(ahi), "r"(blo), "r"(bhi), "r"(acc), "n"(TA), "n"(TB));
}
__device__ __forceinline__ void wgrs80(float (&d)[40], uint32_t a0, uint32_t a1, uint32_t a2, uint32_t a3, uint32_t blo, uint32_t bhi, uint32_t acc) {
    asm volatile("{ .reg .pred p; .reg .b64 db; setp.ne.u32 p, %46, 0; mov.b64 db, {%44, %45};\n"
        "wgmma.mma_async.sync.aligned.m64n80k16.f32.bf16.bf16 {%0, %1, %2, %3, %4, %5, %6, %7, %8, %9, %10, %11, %12, %13, %14, %15, %16, %17, %18, %19, %20, %21, %22, %23, %24, %25, %26, %27, %28, %29, %30, %31, %32, %33, %34, %35, %36, %37, %38, %39}, {%40, %41, %42, %43}, db, p, 1, 1, 0; }"
        : "+f"(d[0]), "+f"(d[1]), "+f"(d[2]), "+f"(d[3]), "+f"(d[4]), "+f"(d[5]), "+f"(d[6]), "+f"(d[7]), "+f"(d[8]), "+f"(d[9]), "+f"(d[10]), "+f"(d[11]), "+f"(d[12]), "+f"(d[13]), "+f"(d[14]), "+f"(d[15]), "+f"(d[16]), "+f"(d[17]), "+f"(d[18]), "+f"(d[19]), "+f"(d[20]), "+f"(d[21]), "+f"(d[22]), "+f"(d[23]), "+f"(d[24]), "+f"(d[25]), "+f"(d[26]), "+f"(d[27]), "+f"(d[28]), "+f"(d[29]), "+f"(d[30]), "+f"(d[31]), "+f"(d[32]), "+f"(d[33]), "+f"(d[34]), "+f"(d[35]), "+f"(d[36]), "+f"(d[37]), "+f"(d[38]), "+f"(d[39]) : "r"(a0), "r"(a1), "r"(a2), "r"(a3), "r"(blo), "r"(bhi), "r"(acc));
}
__device__ __forceinline__ void mb_wait(uint32_t bar, uint32_t parity);
#define SLOWW(b, p, i) mb_wait(b, p)
template <int HX, int L> __device__ __forceinline__ void st_v128(float (&d)[L], uint32_t alo, uint32_t ahi, uint32_t blo, uint32_t bhi, uint32_t first, uint32_t nbar, uint32_t npar, uint32_t pbar, uint32_t xbar, uint32_t ks, int lane) {
    uint32_t ok;
    asm volatile("{ .reg .pred p, f, t; .reg .b64 da, db; .reg .b32 x, y;\n"
        "wgmma.fence.sync.aligned;\n mbarrier.try_wait.parity.shared::cta.b64 p, [%70], %71;\n setp.ne.u32 f, %69, 0; setp.eq.u32 t, 0, 0;\n"
        "add.u32 x, %65, 0; add.u32 y, %67, 0; mov.b64 da, {x, %66}; mov.b64 db, {y, %68};\n wgmma.mma_async.sync.aligned.m64n128k16.f32.bf16.bf16 {%0, %1, %2, %3, %4, %5, %6, %7, %8, %9, %10, %11, %12, %13, %14, %15, %16, %17, %18, %19, %20, %21, %22, %23, %24, %25, %26, %27, %28, %29, %30, %31, %32, %33, %34, %35, %36, %37, %38, %39, %40, %41, %42, %43, %44, %45, %46, %47, %48, %49, %50, %51, %52, %53, %54, %55, %56, %57, %58, %59, %60, %61, %62, %63}, da, db, f, 1, 1, 0, 1;\n"
        "add.u32 x, %65, 2; add.u32 y, %67, 128; mov.b64 da, {x, %66}; mov.b64 db, {y, %68};\n wgmma.mma_async.sync.aligned.m64n128k16.f32.bf16.bf16 {%0, %1, %2, %3, %4, %5, %6, %7, %8, %9, %10, %11, %12, %13, %14, %15, %16, %17, %18, %19, %20, %21, %22, %23, %24, %25, %26, %27, %28, %29, %30, %31, %32, %33, %34, %35, %36, %37, %38, %39, %40, %41, %42, %43, %44, %45, %46, %47, %48, %49, %50, %51, %52, %53, %54, %55, %56, %57, %58, %59, %60, %61, %62, %63}, da, db, t, 1, 1, 0, 1;\n"
        "wgmma.commit_group.sync.aligned;\n selp.u32 %64, 1, 0, p; }"
        : "+f"(d[0]), "+f"(d[1]), "+f"(d[2]), "+f"(d[3]), "+f"(d[4]), "+f"(d[5]), "+f"(d[6]), "+f"(d[7]), "+f"(d[8]), "+f"(d[9]), "+f"(d[10]), "+f"(d[11]), "+f"(d[12]), "+f"(d[13]), "+f"(d[14]), "+f"(d[15]), "+f"(d[16]), "+f"(d[17]), "+f"(d[18]), "+f"(d[19]), "+f"(d[20]), "+f"(d[21]), "+f"(d[22]), "+f"(d[23]), "+f"(d[24]), "+f"(d[25]), "+f"(d[26]), "+f"(d[27]), "+f"(d[28]), "+f"(d[29]), "+f"(d[30]), "+f"(d[31]), "+f"(d[32]), "+f"(d[33]), "+f"(d[34]), "+f"(d[35]), "+f"(d[36]), "+f"(d[37]), "+f"(d[38]), "+f"(d[39]), "+f"(d[40]), "+f"(d[41]), "+f"(d[42]), "+f"(d[43]), "+f"(d[44]), "+f"(d[45]), "+f"(d[46]), "+f"(d[47]), "+f"(d[48]), "+f"(d[49]), "+f"(d[50]), "+f"(d[51]), "+f"(d[52]), "+f"(d[53]), "+f"(d[54]), "+f"(d[55]), "+f"(d[56]), "+f"(d[57]), "+f"(d[58]), "+f"(d[59]), "+f"(d[60]), "+f"(d[61]), "+f"(d[62]), "+f"(d[63]), "=r"(ok) : "r"(alo), "r"(ahi), "r"(blo), "r"(bhi), "r"(first), "r"(nbar), "r"(npar), "r"(ks) : "memory");
    if (__builtin_expect(ok == 0, 0)) SLOWW(nbar, npar, 0);
    if (HX && lane == 0) asm volatile("mbarrier.arrive.shared::cta.b64 _, [%0];" :: "r"(xbar) : "memory");
    asm volatile("wgmma.wait_group.sync.aligned 1;" ::: "memory");
    if (lane == 0) asm volatile("mbarrier.arrive.shared::cta.b64 _, [%0];" :: "r"(pbar) : "memory");
}
template <int HX, int L> __device__ __forceinline__ void st_v160(float (&d)[L], uint32_t alo, uint32_t ahi, uint32_t blo, uint32_t bhi, uint32_t first, uint32_t nbar, uint32_t npar, uint32_t pbar, uint32_t xbar, uint32_t ks, int lane) {
    uint32_t ok;
    asm volatile("{ .reg .pred p, f, t; .reg .b64 da, db; .reg .b32 x, y;\n"
        "wgmma.fence.sync.aligned;\n mbarrier.try_wait.parity.shared::cta.b64 p, [%86], %87;\n setp.ne.u32 f, %85, 0; setp.eq.u32 t, 0, 0;\n"
        "add.u32 x, %81, 0; add.u32 y, %83, 0; mov.b64 da, {x, %82}; mov.b64 db, {y, %84};\n wgmma.mma_async.sync.aligned.m64n160k16.f32.bf16.bf16 {%0, %1, %2, %3, %4, %5, %6, %7, %8, %9, %10, %11, %12, %13, %14, %15, %16, %17, %18, %19, %20, %21, %22, %23, %24, %25, %26, %27, %28, %29, %30, %31, %32, %33, %34, %35, %36, %37, %38, %39, %40, %41, %42, %43, %44, %45, %46, %47, %48, %49, %50, %51, %52, %53, %54, %55, %56, %57, %58, %59, %60, %61, %62, %63, %64, %65, %66, %67, %68, %69, %70, %71, %72, %73, %74, %75, %76, %77, %78, %79}, da, db, f, 1, 1, 0, 1;\n"
        "add.u32 x, %81, 2; add.u32 y, %83, 128; mov.b64 da, {x, %82}; mov.b64 db, {y, %84};\n wgmma.mma_async.sync.aligned.m64n160k16.f32.bf16.bf16 {%0, %1, %2, %3, %4, %5, %6, %7, %8, %9, %10, %11, %12, %13, %14, %15, %16, %17, %18, %19, %20, %21, %22, %23, %24, %25, %26, %27, %28, %29, %30, %31, %32, %33, %34, %35, %36, %37, %38, %39, %40, %41, %42, %43, %44, %45, %46, %47, %48, %49, %50, %51, %52, %53, %54, %55, %56, %57, %58, %59, %60, %61, %62, %63, %64, %65, %66, %67, %68, %69, %70, %71, %72, %73, %74, %75, %76, %77, %78, %79}, da, db, t, 1, 1, 0, 1;\n"
        "wgmma.commit_group.sync.aligned;\n selp.u32 %80, 1, 0, p; }"
        : "+f"(d[0]), "+f"(d[1]), "+f"(d[2]), "+f"(d[3]), "+f"(d[4]), "+f"(d[5]), "+f"(d[6]), "+f"(d[7]), "+f"(d[8]), "+f"(d[9]), "+f"(d[10]), "+f"(d[11]), "+f"(d[12]), "+f"(d[13]), "+f"(d[14]), "+f"(d[15]), "+f"(d[16]), "+f"(d[17]), "+f"(d[18]), "+f"(d[19]), "+f"(d[20]), "+f"(d[21]), "+f"(d[22]), "+f"(d[23]), "+f"(d[24]), "+f"(d[25]), "+f"(d[26]), "+f"(d[27]), "+f"(d[28]), "+f"(d[29]), "+f"(d[30]), "+f"(d[31]), "+f"(d[32]), "+f"(d[33]), "+f"(d[34]), "+f"(d[35]), "+f"(d[36]), "+f"(d[37]), "+f"(d[38]), "+f"(d[39]), "+f"(d[40]), "+f"(d[41]), "+f"(d[42]), "+f"(d[43]), "+f"(d[44]), "+f"(d[45]), "+f"(d[46]), "+f"(d[47]), "+f"(d[48]), "+f"(d[49]), "+f"(d[50]), "+f"(d[51]), "+f"(d[52]), "+f"(d[53]), "+f"(d[54]), "+f"(d[55]), "+f"(d[56]), "+f"(d[57]), "+f"(d[58]), "+f"(d[59]), "+f"(d[60]), "+f"(d[61]), "+f"(d[62]), "+f"(d[63]), "+f"(d[64]), "+f"(d[65]), "+f"(d[66]), "+f"(d[67]), "+f"(d[68]), "+f"(d[69]), "+f"(d[70]), "+f"(d[71]), "+f"(d[72]), "+f"(d[73]), "+f"(d[74]), "+f"(d[75]), "+f"(d[76]), "+f"(d[77]), "+f"(d[78]), "+f"(d[79]), "=r"(ok) : "r"(alo), "r"(ahi), "r"(blo), "r"(bhi), "r"(first), "r"(nbar), "r"(npar), "r"(ks) : "memory");
    if (__builtin_expect(ok == 0, 0)) SLOWW(nbar, npar, 1);
    if (HX && lane == 0) asm volatile("mbarrier.arrive.shared::cta.b64 _, [%0];" :: "r"(xbar) : "memory");
    asm volatile("wgmma.wait_group.sync.aligned 1;" ::: "memory");
    if (lane == 0) asm volatile("mbarrier.arrive.shared::cta.b64 _, [%0];" :: "r"(pbar) : "memory");
}
template <int HX, int L> __device__ __forceinline__ void st_n144(float (&d)[L], uint32_t alo, uint32_t ahi, uint32_t blo, uint32_t bhi, uint32_t first, uint32_t nbar, uint32_t npar, uint32_t pbar, uint32_t xbar, uint32_t ks, int lane) {
    uint32_t ok;
    asm volatile("{ .reg .pred p, f, t; .reg .b64 da, db; .reg .b32 x, y;\n"
        "wgmma.fence.sync.aligned;\n mbarrier.try_wait.parity.shared::cta.b64 p, [%78], %79;\n setp.ne.u32 f, %77, 0; setp.eq.u32 t, 0, 0;\n"
        "mov.b32 x, %73; add.u32 y, %75, 0; mov.b64 da, {x, %74}; mov.b64 db, {y, %76};\n wgmma.mma_async.sync.aligned.m64n144k16.f32.bf16.bf16 {%0, %1, %2, %3, %4, %5, %6, %7, %8, %9, %10, %11, %12, %13, %14, %15, %16, %17, %18, %19, %20, %21, %22, %23, %24, %25, %26, %27, %28, %29, %30, %31, %32, %33, %34, %35, %36, %37, %38, %39, %40, %41, %42, %43, %44, %45, %46, %47, %48, %49, %50, %51, %52, %53, %54, %55, %56, %57, %58, %59, %60, %61, %62, %63, %64, %65, %66, %67, %68, %69, %70, %71}, da, db, f, 1, 1, 0, 0;\n"
        "add.u32 x, x, %80; add.u32 y, %75, 288; mov.b64 da, {x, %74}; mov.b64 db, {y, %76};\n wgmma.mma_async.sync.aligned.m64n144k16.f32.bf16.bf16 {%0, %1, %2, %3, %4, %5, %6, %7, %8, %9, %10, %11, %12, %13, %14, %15, %16, %17, %18, %19, %20, %21, %22, %23, %24, %25, %26, %27, %28, %29, %30, %31, %32, %33, %34, %35, %36, %37, %38, %39, %40, %41, %42, %43, %44, %45, %46, %47, %48, %49, %50, %51, %52, %53, %54, %55, %56, %57, %58, %59, %60, %61, %62, %63, %64, %65, %66, %67, %68, %69, %70, %71}, da, db, t, 1, 1, 0, 0;\n"
        "add.u32 x, x, %80; add.u32 y, %75, 576; mov.b64 da, {x, %74}; mov.b64 db, {y, %76};\n wgmma.mma_async.sync.aligned.m64n144k16.f32.bf16.bf16 {%0, %1, %2, %3, %4, %5, %6, %7, %8, %9, %10, %11, %12, %13, %14, %15, %16, %17, %18, %19, %20, %21, %22, %23, %24, %25, %26, %27, %28, %29, %30, %31, %32, %33, %34, %35, %36, %37, %38, %39, %40, %41, %42, %43, %44, %45, %46, %47, %48, %49, %50, %51, %52, %53, %54, %55, %56, %57, %58, %59, %60, %61, %62, %63, %64, %65, %66, %67, %68, %69, %70, %71}, da, db, t, 1, 1, 0, 0;\n"
        "add.u32 x, x, %80; add.u32 y, %75, 864; mov.b64 da, {x, %74}; mov.b64 db, {y, %76};\n wgmma.mma_async.sync.aligned.m64n144k16.f32.bf16.bf16 {%0, %1, %2, %3, %4, %5, %6, %7, %8, %9, %10, %11, %12, %13, %14, %15, %16, %17, %18, %19, %20, %21, %22, %23, %24, %25, %26, %27, %28, %29, %30, %31, %32, %33, %34, %35, %36, %37, %38, %39, %40, %41, %42, %43, %44, %45, %46, %47, %48, %49, %50, %51, %52, %53, %54, %55, %56, %57, %58, %59, %60, %61, %62, %63, %64, %65, %66, %67, %68, %69, %70, %71}, da, db, t, 1, 1, 0, 0;\n"
        "wgmma.commit_group.sync.aligned;\n selp.u32 %72, 1, 0, p; }"
        : "+f"(d[0]), "+f"(d[1]), "+f"(d[2]), "+f"(d[3]), "+f"(d[4]), "+f"(d[5]), "+f"(d[6]), "+f"(d[7]), "+f"(d[8]), "+f"(d[9]), "+f"(d[10]), "+f"(d[11]), "+f"(d[12]), "+f"(d[13]), "+f"(d[14]), "+f"(d[15]), "+f"(d[16]), "+f"(d[17]), "+f"(d[18]), "+f"(d[19]), "+f"(d[20]), "+f"(d[21]), "+f"(d[22]), "+f"(d[23]), "+f"(d[24]), "+f"(d[25]), "+f"(d[26]), "+f"(d[27]), "+f"(d[28]), "+f"(d[29]), "+f"(d[30]), "+f"(d[31]), "+f"(d[32]), "+f"(d[33]), "+f"(d[34]), "+f"(d[35]), "+f"(d[36]), "+f"(d[37]), "+f"(d[38]), "+f"(d[39]), "+f"(d[40]), "+f"(d[41]), "+f"(d[42]), "+f"(d[43]), "+f"(d[44]), "+f"(d[45]), "+f"(d[46]), "+f"(d[47]), "+f"(d[48]), "+f"(d[49]), "+f"(d[50]), "+f"(d[51]), "+f"(d[52]), "+f"(d[53]), "+f"(d[54]), "+f"(d[55]), "+f"(d[56]), "+f"(d[57]), "+f"(d[58]), "+f"(d[59]), "+f"(d[60]), "+f"(d[61]), "+f"(d[62]), "+f"(d[63]), "+f"(d[64]), "+f"(d[65]), "+f"(d[66]), "+f"(d[67]), "+f"(d[68]), "+f"(d[69]), "+f"(d[70]), "+f"(d[71]), "=r"(ok) : "r"(alo), "r"(ahi), "r"(blo), "r"(bhi), "r"(first), "r"(nbar), "r"(npar), "r"(ks) : "memory");
    if (__builtin_expect(ok == 0, 0)) SLOWW(nbar, npar, 2);
    if (HX && lane == 0) asm volatile("mbarrier.arrive.shared::cta.b64 _, [%0];" :: "r"(xbar) : "memory");
    asm volatile("wgmma.wait_group.sync.aligned 1;" ::: "memory");
    if (lane == 0) asm volatile("mbarrier.arrive.shared::cta.b64 _, [%0];" :: "r"(pbar) : "memory");
}
template <int HX, int L> __device__ __forceinline__ void st_b1(float (&d)[L], uint32_t alo, uint32_t ahi, uint32_t blo, uint32_t bhi, uint32_t first, uint32_t nbar, uint32_t npar, uint32_t pbar, uint32_t xbar, uint32_t ks, int lane) {
    uint32_t ok;
    asm volatile("{ .reg .pred p, f, t; .reg .b64 da, db; .reg .b32 x, y;\n"
        "wgmma.fence.sync.aligned;\n mbarrier.try_wait.parity.shared::cta.b64 p, [%102], %103;\n setp.ne.u32 f, %101, 0; setp.eq.u32 t, 0, 0;\n"
        "add.u32 x, %97, 0; add.u32 y, %99, 0; mov.b64 da, {x, %98}; mov.b64 db, {y, %100};\n wgmma.mma_async.sync.aligned.m64n64k16.f32.bf16.bf16 {%0, %1, %2, %3, %4, %5, %6, %7, %8, %9, %10, %11, %12, %13, %14, %15, %16, %17, %18, %19, %20, %21, %22, %23, %24, %25, %26, %27, %28, %29, %30, %31}, da, db, f, 1, 1, 0, 0;\n"
        "add.u32 x, %97, 512; add.u32 y, %99, 0; mov.b64 da, {x, %98}; mov.b64 db, {y, %100};\n wgmma.mma_async.sync.aligned.m64n64k16.f32.bf16.bf16 {%32, %33, %34, %35, %36, %37, %38, %39, %40, %41, %42, %43, %44, %45, %46, %47, %48, %49, %50, %51, %52, %53, %54, %55, %56, %57, %58, %59, %60, %61, %62, %63}, da, db, f, 1, 1, 0, 0;\n"
        "add.u32 x, %97, 1024; add.u32 y, %99, 0; mov.b64 da, {x, %98}; mov.b64 db, {y, %100};\n wgmma.mma_async.sync.aligned.m64n64k16.f32.bf16.bf16 {%64, %65, %66, %67, %68, %69, %70, %71, %72, %73, %74, %75, %76, %77, %78, %79, %80, %81, %82, %83, %84, %85, %86, %87, %88, %89, %90, %91, %92, %93, %94, %95}, da, db, f, 1, 1, 0, 0;\n"
        "add.u32 x, %97, 2; add.u32 y, %99, 2; mov.b64 da, {x, %98}; mov.b64 db, {y, %100};\n wgmma.mma_async.sync.aligned.m64n64k16.f32.bf16.bf16 {%0, %1, %2, %3, %4, %5, %6, %7, %8, %9, %10, %11, %12, %13, %14, %15, %16, %17, %18, %19, %20, %21, %22, %23, %24, %25, %26, %27, %28, %29, %30, %31}, da, db, t, 1, 1, 0, 0;\n"
        "add.u32 x, %97, 514; add.u32 y, %99, 2; mov.b64 da, {x, %98}; mov.b64 db, {y, %100};\n wgmma.mma_async.sync.aligned.m64n64k16.f32.bf16.bf16 {%32, %33, %34, %35, %36, %37, %38, %39, %40, %41, %42, %43, %44, %45, %46, %47, %48, %49, %50, %51, %52, %53, %54, %55, %56, %57, %58, %59, %60, %61, %62, %63}, da, db, t, 1, 1, 0, 0;\n"
        "add.u32 x, %97, 1026; add.u32 y, %99, 2; mov.b64 da, {x, %98}; mov.b64 db, {y, %100};\n wgmma.mma_async.sync.aligned.m64n64k16.f32.bf16.bf16 {%64, %65, %66, %67, %68, %69, %70, %71, %72, %73, %74, %75, %76, %77, %78, %79, %80, %81, %82, %83, %84, %85, %86, %87, %88, %89, %90, %91, %92, %93, %94, %95}, da, db, t, 1, 1, 0, 0;\n"
        "add.u32 x, %97, 4; add.u32 y, %99, 4; mov.b64 da, {x, %98}; mov.b64 db, {y, %100};\n wgmma.mma_async.sync.aligned.m64n64k16.f32.bf16.bf16 {%0, %1, %2, %3, %4, %5, %6, %7, %8, %9, %10, %11, %12, %13, %14, %15, %16, %17, %18, %19, %20, %21, %22, %23, %24, %25, %26, %27, %28, %29, %30, %31}, da, db, t, 1, 1, 0, 0;\n"
        "add.u32 x, %97, 516; add.u32 y, %99, 4; mov.b64 da, {x, %98}; mov.b64 db, {y, %100};\n wgmma.mma_async.sync.aligned.m64n64k16.f32.bf16.bf16 {%32, %33, %34, %35, %36, %37, %38, %39, %40, %41, %42, %43, %44, %45, %46, %47, %48, %49, %50, %51, %52, %53, %54, %55, %56, %57, %58, %59, %60, %61, %62, %63}, da, db, t, 1, 1, 0, 0;\n"
        "add.u32 x, %97, 1028; add.u32 y, %99, 4; mov.b64 da, {x, %98}; mov.b64 db, {y, %100};\n wgmma.mma_async.sync.aligned.m64n64k16.f32.bf16.bf16 {%64, %65, %66, %67, %68, %69, %70, %71, %72, %73, %74, %75, %76, %77, %78, %79, %80, %81, %82, %83, %84, %85, %86, %87, %88, %89, %90, %91, %92, %93, %94, %95}, da, db, t, 1, 1, 0, 0;\n"
        "add.u32 x, %97, 6; add.u32 y, %99, 6; mov.b64 da, {x, %98}; mov.b64 db, {y, %100};\n wgmma.mma_async.sync.aligned.m64n64k16.f32.bf16.bf16 {%0, %1, %2, %3, %4, %5, %6, %7, %8, %9, %10, %11, %12, %13, %14, %15, %16, %17, %18, %19, %20, %21, %22, %23, %24, %25, %26, %27, %28, %29, %30, %31}, da, db, t, 1, 1, 0, 0;\n"
        "add.u32 x, %97, 518; add.u32 y, %99, 6; mov.b64 da, {x, %98}; mov.b64 db, {y, %100};\n wgmma.mma_async.sync.aligned.m64n64k16.f32.bf16.bf16 {%32, %33, %34, %35, %36, %37, %38, %39, %40, %41, %42, %43, %44, %45, %46, %47, %48, %49, %50, %51, %52, %53, %54, %55, %56, %57, %58, %59, %60, %61, %62, %63}, da, db, t, 1, 1, 0, 0;\n"
        "add.u32 x, %97, 1030; add.u32 y, %99, 6; mov.b64 da, {x, %98}; mov.b64 db, {y, %100};\n wgmma.mma_async.sync.aligned.m64n64k16.f32.bf16.bf16 {%64, %65, %66, %67, %68, %69, %70, %71, %72, %73, %74, %75, %76, %77, %78, %79, %80, %81, %82, %83, %84, %85, %86, %87, %88, %89, %90, %91, %92, %93, %94, %95}, da, db, t, 1, 1, 0, 0;\n"
        "wgmma.commit_group.sync.aligned;\n selp.u32 %96, 1, 0, p; }"
        : "+f"(d[0]), "+f"(d[1]), "+f"(d[2]), "+f"(d[3]), "+f"(d[4]), "+f"(d[5]), "+f"(d[6]), "+f"(d[7]), "+f"(d[8]), "+f"(d[9]), "+f"(d[10]), "+f"(d[11]), "+f"(d[12]), "+f"(d[13]), "+f"(d[14]), "+f"(d[15]), "+f"(d[16]), "+f"(d[17]), "+f"(d[18]), "+f"(d[19]), "+f"(d[20]), "+f"(d[21]), "+f"(d[22]), "+f"(d[23]), "+f"(d[24]), "+f"(d[25]), "+f"(d[26]), "+f"(d[27]), "+f"(d[28]), "+f"(d[29]), "+f"(d[30]), "+f"(d[31]), "+f"(d[32]), "+f"(d[33]), "+f"(d[34]), "+f"(d[35]), "+f"(d[36]), "+f"(d[37]), "+f"(d[38]), "+f"(d[39]), "+f"(d[40]), "+f"(d[41]), "+f"(d[42]), "+f"(d[43]), "+f"(d[44]), "+f"(d[45]), "+f"(d[46]), "+f"(d[47]), "+f"(d[48]), "+f"(d[49]), "+f"(d[50]), "+f"(d[51]), "+f"(d[52]), "+f"(d[53]), "+f"(d[54]), "+f"(d[55]), "+f"(d[56]), "+f"(d[57]), "+f"(d[58]), "+f"(d[59]), "+f"(d[60]), "+f"(d[61]), "+f"(d[62]), "+f"(d[63]), "+f"(d[64]), "+f"(d[65]), "+f"(d[66]), "+f"(d[67]), "+f"(d[68]), "+f"(d[69]), "+f"(d[70]), "+f"(d[71]), "+f"(d[72]), "+f"(d[73]), "+f"(d[74]), "+f"(d[75]), "+f"(d[76]), "+f"(d[77]), "+f"(d[78]), "+f"(d[79]), "+f"(d[80]), "+f"(d[81]), "+f"(d[82]), "+f"(d[83]), "+f"(d[84]), "+f"(d[85]), "+f"(d[86]), "+f"(d[87]), "+f"(d[88]), "+f"(d[89]), "+f"(d[90]), "+f"(d[91]), "+f"(d[92]), "+f"(d[93]), "+f"(d[94]), "+f"(d[95]), "=r"(ok) : "r"(alo), "r"(ahi), "r"(blo), "r"(bhi), "r"(first), "r"(nbar), "r"(npar), "r"(ks) : "memory");
    if (__builtin_expect(ok == 0, 0)) SLOWW(nbar, npar, 3);
    if (HX && lane == 0) asm volatile("mbarrier.arrive.shared::cta.b64 _, [%0];" :: "r"(xbar) : "memory");
    asm volatile("wgmma.wait_group.sync.aligned 1;" ::: "memory");
    if (lane == 0) asm volatile("mbarrier.arrive.shared::cta.b64 _, [%0], 2;" :: "r"(pbar) : "memory");
}
template <int HX, int L> __device__ __forceinline__ void st_b2d(float (&d)[L], uint32_t alo, uint32_t ahi, uint32_t blo, uint32_t bhi, uint32_t first, uint32_t nbar, uint32_t npar, uint32_t pbar, uint32_t xbar, uint32_t ks, int lane) {
    uint32_t ok;
    asm volatile("{ .reg .pred p, f, t; .reg .b64 da, db; .reg .b32 x, y;\n"
        "wgmma.fence.sync.aligned;\n mbarrier.try_wait.parity.shared::cta.b64 p, [%102], %103;\n setp.ne.u32 f, %101, 0; setp.eq.u32 t, 0, 0;\n"
        "add.u32 x, %97, 0; add.u32 y, %99, 0; mov.b64 da, {x, %98}; mov.b64 db, {y, %100};\n wgmma.mma_async.sync.aligned.m64n192k16.f32.bf16.bf16 {%0, %1, %2, %3, %4, %5, %6, %7, %8, %9, %10, %11, %12, %13, %14, %15, %16, %17, %18, %19, %20, %21, %22, %23, %24, %25, %26, %27, %28, %29, %30, %31, %32, %33, %34, %35, %36, %37, %38, %39, %40, %41, %42, %43, %44, %45, %46, %47, %48, %49, %50, %51, %52, %53, %54, %55, %56, %57, %58, %59, %60, %61, %62, %63, %64, %65, %66, %67, %68, %69, %70, %71, %72, %73, %74, %75, %76, %77, %78, %79, %80, %81, %82, %83, %84, %85, %86, %87, %88, %89, %90, %91, %92, %93, %94, %95}, da, db, t, 1, 1, 1, 0;\n"
        "add.u32 x, %97, 128; add.u32 y, %99, 2; mov.b64 da, {x, %98}; mov.b64 db, {y, %100};\n wgmma.mma_async.sync.aligned.m64n192k16.f32.bf16.bf16 {%0, %1, %2, %3, %4, %5, %6, %7, %8, %9, %10, %11, %12, %13, %14, %15, %16, %17, %18, %19, %20, %21, %22, %23, %24, %25, %26, %27, %28, %29, %30, %31, %32, %33, %34, %35, %36, %37, %38, %39, %40, %41, %42, %43, %44, %45, %46, %47, %48, %49, %50, %51, %52, %53, %54, %55, %56, %57, %58, %59, %60, %61, %62, %63, %64, %65, %66, %67, %68, %69, %70, %71, %72, %73, %74, %75, %76, %77, %78, %79, %80, %81, %82, %83, %84, %85, %86, %87, %88, %89, %90, %91, %92, %93, %94, %95}, da, db, t, 1, 1, 1, 0;\n"
        "add.u32 x, %97, 256; add.u32 y, %99, 4; mov.b64 da, {x, %98}; mov.b64 db, {y, %100};\n wgmma.mma_async.sync.aligned.m64n192k16.f32.bf16.bf16 {%0, %1, %2, %3, %4, %5, %6, %7, %8, %9, %10, %11, %12, %13, %14, %15, %16, %17, %18, %19, %20, %21, %22, %23, %24, %25, %26, %27, %28, %29, %30, %31, %32, %33, %34, %35, %36, %37, %38, %39, %40, %41, %42, %43, %44, %45, %46, %47, %48, %49, %50, %51, %52, %53, %54, %55, %56, %57, %58, %59, %60, %61, %62, %63, %64, %65, %66, %67, %68, %69, %70, %71, %72, %73, %74, %75, %76, %77, %78, %79, %80, %81, %82, %83, %84, %85, %86, %87, %88, %89, %90, %91, %92, %93, %94, %95}, da, db, t, 1, 1, 1, 0;\n"
        "add.u32 x, %97, 384; add.u32 y, %99, 6; mov.b64 da, {x, %98}; mov.b64 db, {y, %100};\n wgmma.mma_async.sync.aligned.m64n192k16.f32.bf16.bf16 {%0, %1, %2, %3, %4, %5, %6, %7, %8, %9, %10, %11, %12, %13, %14, %15, %16, %17, %18, %19, %20, %21, %22, %23, %24, %25, %26, %27, %28, %29, %30, %31, %32, %33, %34, %35, %36, %37, %38, %39, %40, %41, %42, %43, %44, %45, %46, %47, %48, %49, %50, %51, %52, %53, %54, %55, %56, %57, %58, %59, %60, %61, %62, %63, %64, %65, %66, %67, %68, %69, %70, %71, %72, %73, %74, %75, %76, %77, %78, %79, %80, %81, %82, %83, %84, %85, %86, %87, %88, %89, %90, %91, %92, %93, %94, %95}, da, db, t, 1, 1, 1, 0;\n"
        "wgmma.commit_group.sync.aligned;\n selp.u32 %96, 1, 0, p; }"
        : "+f"(d[0]), "+f"(d[1]), "+f"(d[2]), "+f"(d[3]), "+f"(d[4]), "+f"(d[5]), "+f"(d[6]), "+f"(d[7]), "+f"(d[8]), "+f"(d[9]), "+f"(d[10]), "+f"(d[11]), "+f"(d[12]), "+f"(d[13]), "+f"(d[14]), "+f"(d[15]), "+f"(d[16]), "+f"(d[17]), "+f"(d[18]), "+f"(d[19]), "+f"(d[20]), "+f"(d[21]), "+f"(d[22]), "+f"(d[23]), "+f"(d[24]), "+f"(d[25]), "+f"(d[26]), "+f"(d[27]), "+f"(d[28]), "+f"(d[29]), "+f"(d[30]), "+f"(d[31]), "+f"(d[32]), "+f"(d[33]), "+f"(d[34]), "+f"(d[35]), "+f"(d[36]), "+f"(d[37]), "+f"(d[38]), "+f"(d[39]), "+f"(d[40]), "+f"(d[41]), "+f"(d[42]), "+f"(d[43]), "+f"(d[44]), "+f"(d[45]), "+f"(d[46]), "+f"(d[47]), "+f"(d[48]), "+f"(d[49]), "+f"(d[50]), "+f"(d[51]), "+f"(d[52]), "+f"(d[53]), "+f"(d[54]), "+f"(d[55]), "+f"(d[56]), "+f"(d[57]), "+f"(d[58]), "+f"(d[59]), "+f"(d[60]), "+f"(d[61]), "+f"(d[62]), "+f"(d[63]), "+f"(d[64]), "+f"(d[65]), "+f"(d[66]), "+f"(d[67]), "+f"(d[68]), "+f"(d[69]), "+f"(d[70]), "+f"(d[71]), "+f"(d[72]), "+f"(d[73]), "+f"(d[74]), "+f"(d[75]), "+f"(d[76]), "+f"(d[77]), "+f"(d[78]), "+f"(d[79]), "+f"(d[80]), "+f"(d[81]), "+f"(d[82]), "+f"(d[83]), "+f"(d[84]), "+f"(d[85]), "+f"(d[86]), "+f"(d[87]), "+f"(d[88]), "+f"(d[89]), "+f"(d[90]), "+f"(d[91]), "+f"(d[92]), "+f"(d[93]), "+f"(d[94]), "+f"(d[95]), "=r"(ok) : "r"(alo), "r"(ahi), "r"(blo), "r"(bhi), "r"(first), "r"(nbar), "r"(npar), "r"(ks) : "memory");
    if (__builtin_expect(ok == 0, 0)) SLOWW(nbar, npar, 4);
    if (HX && lane == 0) asm volatile("mbarrier.arrive.shared::cta.b64 _, [%0];" :: "r"(xbar) : "memory");
    asm volatile("wgmma.wait_group.sync.aligned 1;" ::: "memory");
    if (lane == 0) asm volatile("mbarrier.arrive.shared::cta.b64 _, [%0], 2;" :: "r"(pbar) : "memory");
}
template <int HX, int L> __device__ __forceinline__ void st_b2e(float (&d)[L], uint32_t alo, uint32_t ahi, uint32_t blo, uint32_t bhi, uint32_t first, uint32_t nbar, uint32_t npar, uint32_t pbar, uint32_t xbar, uint32_t ks, int lane) {
    uint32_t ok;
    asm volatile("{ .reg .pred p, f, t; .reg .b64 da, db; .reg .b32 x, y;\n"
        "wgmma.fence.sync.aligned;\n mbarrier.try_wait.parity.shared::cta.b64 p, [%102], %103;\n setp.ne.u32 f, %101, 0; setp.eq.u32 t, 0, 0;\n"
        "add.u32 x, %97, 0; add.u32 y, %99, 0; mov.b64 da, {x, %98}; mov.b64 db, {y, %100};\n wgmma.mma_async.sync.aligned.m64n192k16.f32.bf16.bf16 {%0, %1, %2, %3, %4, %5, %6, %7, %8, %9, %10, %11, %12, %13, %14, %15, %16, %17, %18, %19, %20, %21, %22, %23, %24, %25, %26, %27, %28, %29, %30, %31, %32, %33, %34, %35, %36, %37, %38, %39, %40, %41, %42, %43, %44, %45, %46, %47, %48, %49, %50, %51, %52, %53, %54, %55, %56, %57, %58, %59, %60, %61, %62, %63, %64, %65, %66, %67, %68, %69, %70, %71, %72, %73, %74, %75, %76, %77, %78, %79, %80, %81, %82, %83, %84, %85, %86, %87, %88, %89, %90, %91, %92, %93, %94, %95}, da, db, t, 1, 1, 1, 0;\n"
        "add.u32 x, %97, 128; add.u32 y, %99, 2; mov.b64 da, {x, %98}; mov.b64 db, {y, %100};\n wgmma.mma_async.sync.aligned.m64n192k16.f32.bf16.bf16 {%0, %1, %2, %3, %4, %5, %6, %7, %8, %9, %10, %11, %12, %13, %14, %15, %16, %17, %18, %19, %20, %21, %22, %23, %24, %25, %26, %27, %28, %29, %30, %31, %32, %33, %34, %35, %36, %37, %38, %39, %40, %41, %42, %43, %44, %45, %46, %47, %48, %49, %50, %51, %52, %53, %54, %55, %56, %57, %58, %59, %60, %61, %62, %63, %64, %65, %66, %67, %68, %69, %70, %71, %72, %73, %74, %75, %76, %77, %78, %79, %80, %81, %82, %83, %84, %85, %86, %87, %88, %89, %90, %91, %92, %93, %94, %95}, da, db, t, 1, 1, 1, 0;\n"
        "wgmma.commit_group.sync.aligned;\n selp.u32 %96, 1, 0, p; }"
        : "+f"(d[0]), "+f"(d[1]), "+f"(d[2]), "+f"(d[3]), "+f"(d[4]), "+f"(d[5]), "+f"(d[6]), "+f"(d[7]), "+f"(d[8]), "+f"(d[9]), "+f"(d[10]), "+f"(d[11]), "+f"(d[12]), "+f"(d[13]), "+f"(d[14]), "+f"(d[15]), "+f"(d[16]), "+f"(d[17]), "+f"(d[18]), "+f"(d[19]), "+f"(d[20]), "+f"(d[21]), "+f"(d[22]), "+f"(d[23]), "+f"(d[24]), "+f"(d[25]), "+f"(d[26]), "+f"(d[27]), "+f"(d[28]), "+f"(d[29]), "+f"(d[30]), "+f"(d[31]), "+f"(d[32]), "+f"(d[33]), "+f"(d[34]), "+f"(d[35]), "+f"(d[36]), "+f"(d[37]), "+f"(d[38]), "+f"(d[39]), "+f"(d[40]), "+f"(d[41]), "+f"(d[42]), "+f"(d[43]), "+f"(d[44]), "+f"(d[45]), "+f"(d[46]), "+f"(d[47]), "+f"(d[48]), "+f"(d[49]), "+f"(d[50]), "+f"(d[51]), "+f"(d[52]), "+f"(d[53]), "+f"(d[54]), "+f"(d[55]), "+f"(d[56]), "+f"(d[57]), "+f"(d[58]), "+f"(d[59]), "+f"(d[60]), "+f"(d[61]), "+f"(d[62]), "+f"(d[63]), "+f"(d[64]), "+f"(d[65]), "+f"(d[66]), "+f"(d[67]), "+f"(d[68]), "+f"(d[69]), "+f"(d[70]), "+f"(d[71]), "+f"(d[72]), "+f"(d[73]), "+f"(d[74]), "+f"(d[75]), "+f"(d[76]), "+f"(d[77]), "+f"(d[78]), "+f"(d[79]), "+f"(d[80]), "+f"(d[81]), "+f"(d[82]), "+f"(d[83]), "+f"(d[84]), "+f"(d[85]), "+f"(d[86]), "+f"(d[87]), "+f"(d[88]), "+f"(d[89]), "+f"(d[90]), "+f"(d[91]), "+f"(d[92]), "+f"(d[93]), "+f"(d[94]), "+f"(d[95]), "=r"(ok) : "r"(alo), "r"(ahi), "r"(blo), "r"(bhi), "r"(first), "r"(nbar), "r"(npar), "r"(ks) : "memory");
    if (__builtin_expect(ok == 0, 0)) SLOWW(nbar, npar, 5);
    if (HX && lane == 0) asm volatile("mbarrier.arrive.shared::cta.b64 _, [%0];" :: "r"(xbar) : "memory");
    asm volatile("wgmma.wait_group.sync.aligned 1;" ::: "memory");
    if (lane == 0) asm volatile("mbarrier.arrive.shared::cta.b64 _, [%0], 2;" :: "r"(pbar) : "memory");
}
template <int HX, int L> __device__ __forceinline__ void st_b2s(float (&d)[L], uint32_t alo, uint32_t ahi, uint32_t blo, uint32_t bhi, uint32_t first, uint32_t nbar, uint32_t npar, uint32_t pbar, uint32_t xbar, uint32_t ks, int lane) {
    uint32_t ok;
    asm volatile("{ .reg .pred p, f, t; .reg .b64 da, db; .reg .b32 x, y;\n"
        "wgmma.fence.sync.aligned;\n mbarrier.try_wait.parity.shared::cta.b64 p, [%54], %55;\n setp.ne.u32 f, %53, 0; setp.eq.u32 t, 0, 0;\n"
        "add.u32 x, %49, 0; add.u32 y, %51, 0; mov.b64 da, {x, %50}; mov.b64 db, {y, %52};\n wgmma.mma_async.sync.aligned.m64n96k16.f32.bf16.bf16 {%0, %1, %2, %3, %4, %5, %6, %7, %8, %9, %10, %11, %12, %13, %14, %15, %16, %17, %18, %19, %20, %21, %22, %23, %24, %25, %26, %27, %28, %29, %30, %31, %32, %33, %34, %35, %36, %37, %38, %39, %40, %41, %42, %43, %44, %45, %46, %47}, da, db, f, 1, 1, 1, 0;\n"
        "add.u32 x, %49, 128; add.u32 y, %51, 2; mov.b64 da, {x, %50}; mov.b64 db, {y, %52};\n wgmma.mma_async.sync.aligned.m64n96k16.f32.bf16.bf16 {%0, %1, %2, %3, %4, %5, %6, %7, %8, %9, %10, %11, %12, %13, %14, %15, %16, %17, %18, %19, %20, %21, %22, %23, %24, %25, %26, %27, %28, %29, %30, %31, %32, %33, %34, %35, %36, %37, %38, %39, %40, %41, %42, %43, %44, %45, %46, %47}, da, db, t, 1, 1, 1, 0;\n"
        "add.u32 x, %49, 256; add.u32 y, %51, 4; mov.b64 da, {x, %50}; mov.b64 db, {y, %52};\n wgmma.mma_async.sync.aligned.m64n96k16.f32.bf16.bf16 {%0, %1, %2, %3, %4, %5, %6, %7, %8, %9, %10, %11, %12, %13, %14, %15, %16, %17, %18, %19, %20, %21, %22, %23, %24, %25, %26, %27, %28, %29, %30, %31, %32, %33, %34, %35, %36, %37, %38, %39, %40, %41, %42, %43, %44, %45, %46, %47}, da, db, t, 1, 1, 1, 0;\n"
        "add.u32 x, %49, 384; add.u32 y, %51, 6; mov.b64 da, {x, %50}; mov.b64 db, {y, %52};\n wgmma.mma_async.sync.aligned.m64n96k16.f32.bf16.bf16 {%0, %1, %2, %3, %4, %5, %6, %7, %8, %9, %10, %11, %12, %13, %14, %15, %16, %17, %18, %19, %20, %21, %22, %23, %24, %25, %26, %27, %28, %29, %30, %31, %32, %33, %34, %35, %36, %37, %38, %39, %40, %41, %42, %43, %44, %45, %46, %47}, da, db, t, 1, 1, 1, 0;\n"
        "add.u32 x, %49, 512; add.u32 y, %51, 768; mov.b64 da, {x, %50}; mov.b64 db, {y, %52};\n wgmma.mma_async.sync.aligned.m64n96k16.f32.bf16.bf16 {%0, %1, %2, %3, %4, %5, %6, %7, %8, %9, %10, %11, %12, %13, %14, %15, %16, %17, %18, %19, %20, %21, %22, %23, %24, %25, %26, %27, %28, %29, %30, %31, %32, %33, %34, %35, %36, %37, %38, %39, %40, %41, %42, %43, %44, %45, %46, %47}, da, db, t, 1, 1, 1, 0;\n"
        "add.u32 x, %49, 640; add.u32 y, %51, 770; mov.b64 da, {x, %50}; mov.b64 db, {y, %52};\n wgmma.mma_async.sync.aligned.m64n96k16.f32.bf16.bf16 {%0, %1, %2, %3, %4, %5, %6, %7, %8, %9, %10, %11, %12, %13, %14, %15, %16, %17, %18, %19, %20, %21, %22, %23, %24, %25, %26, %27, %28, %29, %30, %31, %32, %33, %34, %35, %36, %37, %38, %39, %40, %41, %42, %43, %44, %45, %46, %47}, da, db, t, 1, 1, 1, 0;\n"
        "add.u32 x, %49, 768; add.u32 y, %51, 772; mov.b64 da, {x, %50}; mov.b64 db, {y, %52};\n wgmma.mma_async.sync.aligned.m64n96k16.f32.bf16.bf16 {%0, %1, %2, %3, %4, %5, %6, %7, %8, %9, %10, %11, %12, %13, %14, %15, %16, %17, %18, %19, %20, %21, %22, %23, %24, %25, %26, %27, %28, %29, %30, %31, %32, %33, %34, %35, %36, %37, %38, %39, %40, %41, %42, %43, %44, %45, %46, %47}, da, db, t, 1, 1, 1, 0;\n"
        "add.u32 x, %49, 896; add.u32 y, %51, 774; mov.b64 da, {x, %50}; mov.b64 db, {y, %52};\n wgmma.mma_async.sync.aligned.m64n96k16.f32.bf16.bf16 {%0, %1, %2, %3, %4, %5, %6, %7, %8, %9, %10, %11, %12, %13, %14, %15, %16, %17, %18, %19, %20, %21, %22, %23, %24, %25, %26, %27, %28, %29, %30, %31, %32, %33, %34, %35, %36, %37, %38, %39, %40, %41, %42, %43, %44, %45, %46, %47}, da, db, t, 1, 1, 1, 0;\n"
        "wgmma.commit_group.sync.aligned;\n selp.u32 %48, 1, 0, p; }"
        : "+f"(d[0]), "+f"(d[1]), "+f"(d[2]), "+f"(d[3]), "+f"(d[4]), "+f"(d[5]), "+f"(d[6]), "+f"(d[7]), "+f"(d[8]), "+f"(d[9]), "+f"(d[10]), "+f"(d[11]), "+f"(d[12]), "+f"(d[13]), "+f"(d[14]), "+f"(d[15]), "+f"(d[16]), "+f"(d[17]), "+f"(d[18]), "+f"(d[19]), "+f"(d[20]), "+f"(d[21]), "+f"(d[22]), "+f"(d[23]), "+f"(d[24]), "+f"(d[25]), "+f"(d[26]), "+f"(d[27]), "+f"(d[28]), "+f"(d[29]), "+f"(d[30]), "+f"(d[31]), "+f"(d[32]), "+f"(d[33]), "+f"(d[34]), "+f"(d[35]), "+f"(d[36]), "+f"(d[37]), "+f"(d[38]), "+f"(d[39]), "+f"(d[40]), "+f"(d[41]), "+f"(d[42]), "+f"(d[43]), "+f"(d[44]), "+f"(d[45]), "+f"(d[46]), "+f"(d[47]), "=r"(ok) : "r"(alo), "r"(ahi), "r"(blo), "r"(bhi), "r"(first), "r"(nbar), "r"(npar), "r"(ks) : "memory");
    if (__builtin_expect(ok == 0, 0)) SLOWW(nbar, npar, 6);
    if (HX && lane == 0) asm volatile("mbarrier.arrive.shared::cta.b64 _, [%0];" :: "r"(xbar) : "memory");
    asm volatile("wgmma.wait_group.sync.aligned 1;" ::: "memory");
    if (lane == 0) asm volatile("mbarrier.arrive.shared::cta.b64 _, [%0], 2;" :: "r"(pbar) : "memory");
}
template <int HX, int L> __device__ __forceinline__ void st_b2t(float (&d)[L], uint32_t alo, uint32_t ahi, uint32_t blo, uint32_t bhi, uint32_t first, uint32_t nbar, uint32_t npar, uint32_t pbar, uint32_t xbar, uint32_t ks, int lane) {
    uint32_t ok;
    asm volatile("{ .reg .pred p, f, t; .reg .b64 da, db; .reg .b32 x, y;\n"
        "wgmma.fence.sync.aligned;\n mbarrier.try_wait.parity.shared::cta.b64 p, [%54], %55;\n setp.ne.u32 f, %53, 0; setp.eq.u32 t, 0, 0;\n"
        "add.u32 x, %49, 0; add.u32 y, %51, 0; mov.b64 da, {x, %50}; mov.b64 db, {y, %52};\n wgmma.mma_async.sync.aligned.m64n96k16.f32.bf16.bf16 {%0, %1, %2, %3, %4, %5, %6, %7, %8, %9, %10, %11, %12, %13, %14, %15, %16, %17, %18, %19, %20, %21, %22, %23, %24, %25, %26, %27, %28, %29, %30, %31, %32, %33, %34, %35, %36, %37, %38, %39, %40, %41, %42, %43, %44, %45, %46, %47}, da, db, t, 1, 1, 1, 0;\n"
        "add.u32 x, %49, 128; add.u32 y, %51, 2; mov.b64 da, {x, %50}; mov.b64 db, {y, %52};\n wgmma.mma_async.sync.aligned.m64n96k16.f32.bf16.bf16 {%0, %1, %2, %3, %4, %5, %6, %7, %8, %9, %10, %11, %12, %13, %14, %15, %16, %17, %18, %19, %20, %21, %22, %23, %24, %25, %26, %27, %28, %29, %30, %31, %32, %33, %34, %35, %36, %37, %38, %39, %40, %41, %42, %43, %44, %45, %46, %47}, da, db, t, 1, 1, 1, 0;\n"
        "add.u32 x, %49, 256; add.u32 y, %51, 768; mov.b64 da, {x, %50}; mov.b64 db, {y, %52};\n wgmma.mma_async.sync.aligned.m64n96k16.f32.bf16.bf16 {%0, %1, %2, %3, %4, %5, %6, %7, %8, %9, %10, %11, %12, %13, %14, %15, %16, %17, %18, %19, %20, %21, %22, %23, %24, %25, %26, %27, %28, %29, %30, %31, %32, %33, %34, %35, %36, %37, %38, %39, %40, %41, %42, %43, %44, %45, %46, %47}, da, db, t, 1, 1, 1, 0;\n"
        "add.u32 x, %49, 384; add.u32 y, %51, 770; mov.b64 da, {x, %50}; mov.b64 db, {y, %52};\n wgmma.mma_async.sync.aligned.m64n96k16.f32.bf16.bf16 {%0, %1, %2, %3, %4, %5, %6, %7, %8, %9, %10, %11, %12, %13, %14, %15, %16, %17, %18, %19, %20, %21, %22, %23, %24, %25, %26, %27, %28, %29, %30, %31, %32, %33, %34, %35, %36, %37, %38, %39, %40, %41, %42, %43, %44, %45, %46, %47}, da, db, t, 1, 1, 1, 0;\n"
        "wgmma.commit_group.sync.aligned;\n selp.u32 %48, 1, 0, p; }"
        : "+f"(d[0]), "+f"(d[1]), "+f"(d[2]), "+f"(d[3]), "+f"(d[4]), "+f"(d[5]), "+f"(d[6]), "+f"(d[7]), "+f"(d[8]), "+f"(d[9]), "+f"(d[10]), "+f"(d[11]), "+f"(d[12]), "+f"(d[13]), "+f"(d[14]), "+f"(d[15]), "+f"(d[16]), "+f"(d[17]), "+f"(d[18]), "+f"(d[19]), "+f"(d[20]), "+f"(d[21]), "+f"(d[22]), "+f"(d[23]), "+f"(d[24]), "+f"(d[25]), "+f"(d[26]), "+f"(d[27]), "+f"(d[28]), "+f"(d[29]), "+f"(d[30]), "+f"(d[31]), "+f"(d[32]), "+f"(d[33]), "+f"(d[34]), "+f"(d[35]), "+f"(d[36]), "+f"(d[37]), "+f"(d[38]), "+f"(d[39]), "+f"(d[40]), "+f"(d[41]), "+f"(d[42]), "+f"(d[43]), "+f"(d[44]), "+f"(d[45]), "+f"(d[46]), "+f"(d[47]), "=r"(ok) : "r"(alo), "r"(ahi), "r"(blo), "r"(bhi), "r"(first), "r"(nbar), "r"(npar), "r"(ks) : "memory");
    if (__builtin_expect(ok == 0, 0)) SLOWW(nbar, npar, 7);
    if (HX && lane == 0) asm volatile("mbarrier.arrive.shared::cta.b64 _, [%0];" :: "r"(xbar) : "memory");
    asm volatile("wgmma.wait_group.sync.aligned 1;" ::: "memory");
    if (lane == 0) asm volatile("mbarrier.arrive.shared::cta.b64 _, [%0], 2;" :: "r"(pbar) : "memory");
}

__device__ uint4 g_wimg[2 * 108 * 576];
__device__ float4 g_kvacc[2][32 * 180];
__device__ uint4 g_agg[2][24 * 192];
__device__ unsigned g_cnt[20 * 32];
__device__ unsigned g_epoch;
#define CNT_K 0
#define CNT_WO 4
#define CNT_KV 6

#define PST(i)
#define PSTP(i)
#define PACC(i, v)
#define TW(x) x
#define TG(x) x

struct __align__(64) Params {
    CUtensorMap m[11];
    const uint8_t* wphi; const uint32_t* wo; const uint8_t* cw[2];
    const uint2* xb; const unsigned short* lre; const unsigned short* lim; const unsigned short* ldt; const uint2* dsk;
    float* out; int swap;
    uint32_t b2[2][30];
};

#define SB0 0x400u
#define BAR 230400u
#define A_AUX 110592u
#define A_PHI (A_AUX + 21504u)
#define A_ST1(i) ((i) == 1 ? 42624u : A_AUX + 40064u)
#define A_ST0(i) ((i) & 1 ? A_ST1(i) - 5760u : A_AUX + 1024u)
#define A_X 156672u
#define B_HD 122880u
#define B_X 155648u
#define B_RECV (B_HD + 9u * 8192u)
#define R1(s) (16u * (s))
#define R2(s) (128u + 16u * (s))
#define TOK(i) (320u + 8u * (i))
#define SIG(i) (384u + 8u * (i))
#define NUMD(i) (424u + 8u * (i))
#define KVD(i) (440u + 8u * (i))
#define KRD(i) (472u + 8u * (i))
#define BD(i) (R2(6 + (i)) + 8u)
#define HR(i) (440u + 8u * (i))
#define EPO 512u
#define RDY(i) (520u + 8u * (i))
#define KVR(i) (536u + 8u * (i))
#define PART(i) (568u + 8u * (i))
#define RFULL(i) (520u + 8u * (i))
#define FLD 120u
#define BXF 128u
#define FRD 552u
#define BXD 560u
#define AXF(i) (704u + 8u * (i))
#define VST 640u
#define RFREE(i) (640u + 8u * (i))
#define XD(i) (664u + 8u * (i))
#define DONE 680u
#define FSIG 688u
#define EPOVAL 696u
#define DUMMY 112u

#define DHI_SW 0x40000040u

__device__ __forceinline__ void mb_init(uint32_t bar, uint32_t cnt) { asm volatile("mbarrier.init.shared::cta.b64 [%0], %1;" :: "r"(bar), "r"(cnt) : "memory"); }
__device__ __forceinline__ void mb_expect(uint32_t bar, uint32_t bytes) { asm volatile("mbarrier.arrive.expect_tx.shared::cta.b64 _, [%0], %1;" :: "r"(bar), "r"(bytes) : "memory"); }
__device__ __forceinline__ void mb_arrive(uint32_t bar) { asm volatile("mbarrier.arrive.shared::cta.b64 _, [%0];" :: "r"(bar) : "memory"); }
__device__ __forceinline__ void mb_arrive_n(uint32_t bar, uint32_t n) { asm volatile("mbarrier.arrive.shared::cta.b64 _, [%0], %1;" :: "r"(bar), "r"(n) : "memory"); }
__device__ __forceinline__ void mb_arrive_rem(uint32_t bar, uint32_t n) { asm volatile("mbarrier.arrive.shared::cluster.b64 _, [%0], %1;" :: "r"(bar), "r"(n) : "memory"); }
__device__ __forceinline__ void mb_wait(uint32_t bar, uint32_t parity) {
    asm volatile("{ .reg .pred p;\n LW: mbarrier.try_wait.parity.shared::cta.b64 p, [%0], %1;\n @!p bra LW; }" :: "r"(bar), "r"(parity) : "memory");
}
__device__ __forceinline__ void mb_wait_cl(uint32_t bar, uint32_t parity) {
    asm volatile("{ .reg .pred p;\n LW: mbarrier.try_wait.parity.acquire.cluster.shared::cta.b64 p, [%0], %1;\n @!p bra LW; }" :: "r"(bar), "r"(parity) : "memory");
}
__device__ __forceinline__ void mb_wait_b(uint32_t bar) {
    asm volatile("{ .reg .pred p; .reg .u32 c; mov.u32 c, 0;\n"
                 "LW: mbarrier.try_wait.parity.shared::cta.b64 p, [%0], 0, 1000;\n"
                 "@p bra LD;\n add.u32 c, c, 1; setp.lt.u32 p, c, 200000; @p bra LW; trap;\n LD: }" :: "r"(bar) : "memory");
}
__device__ __forceinline__ void wg_fence() { asm volatile("wgmma.fence.sync.aligned;" ::: "memory"); }
__device__ __forceinline__ void wg_commit() { asm volatile("wgmma.commit_group.sync.aligned;" ::: "memory"); }
template <int N> __device__ __forceinline__ void wg_wait() { asm volatile("wgmma.wait_group.sync.aligned %0;" :: "n"(N) : "memory"); }
template <int L> __device__ __forceinline__ void reg_fence(float (&d)[L]) {
#pragma unroll
    for (int i = 0; i < L; i++) asm volatile("" : "+f"(d[i]) :: "memory");
}
template <int L> __device__ __forceinline__ void reg_def(float (&d)[L]) {
#pragma unroll
    for (int i = 0; i < L; i++) asm volatile("{ .reg .f32 t; mov.f32 %0, t; }" : "=f"(d[i]));
}
__device__ __forceinline__ void proxy_fence() { asm volatile("fence.proxy.async.shared::cta;" ::: "memory"); }
__device__ __forceinline__ void proxy_fence_g() { asm volatile("fence.proxy.async.global;" ::: "memory"); }
__device__ __forceinline__ void wg_bar(int wg) { asm volatile("bar.sync %0, 128;" :: "r"(wg + 1) : "memory"); }
__device__ __forceinline__ bool elect_one() { uint32_t p; asm volatile("{ .reg .pred P; elect.sync _|P, 0xffffffff; selp.u32 %0, 1, 0, P; }" : "=r"(p)); return p; }
__device__ __forceinline__ void cl_arrive() { asm volatile("barrier.cluster.arrive.relaxed.aligned;" ::: "memory"); }
__device__ __forceinline__ void cl_wait() { asm volatile("barrier.cluster.wait.aligned;" ::: "memory"); }
__device__ __forceinline__ uint32_t pack2(float lo, float hi) { uint32_t r; asm("cvt.rn.bf16x2.f32 %0, %1, %2;" : "=r"(r) : "f"(hi), "f"(lo)); return r; }
__device__ __forceinline__ float ex2f(float x) { float r; asm("ex2.approx.ftz.f32 %0, %1;" : "=f"(r) : "f"(x)); return r; }
__device__ __forceinline__ float rcpf(float x) { float r; asm("rcp.approx.ftz.f32 %0, %1;" : "=f"(r) : "f"(x)); return r; }
__device__ __forceinline__ void sts128(uint32_t a, uint32_t x, uint32_t y, uint32_t z, uint32_t w) { asm volatile("st.shared.v4.b32 [%0], {%1, %2, %3, %4};" :: "r"(a), "r"(x), "r"(y), "r"(z), "r"(w) : "memory"); }
__device__ __forceinline__ void sts64(uint32_t a, uint32_t x, uint32_t y) { asm volatile("st.shared.v2.b32 [%0], {%1, %2};" :: "r"(a), "r"(x), "r"(y) : "memory"); }
__device__ __forceinline__ void stsm4(uint32_t a, uint32_t x, uint32_t y, uint32_t z, uint32_t w) { asm volatile("stmatrix.sync.aligned.m8n8.x4.shared.b16 [%0], {%1, %2, %3, %4};" :: "r"(a), "r"(x), "r"(y), "r"(z), "r"(w) : "memory"); }
__device__ __forceinline__ void stsm2(uint32_t a, uint32_t x, uint32_t y) { asm volatile("stmatrix.sync.aligned.m8n8.x2.shared.b16 [%0], {%1, %2};" :: "r"(a), "r"(x), "r"(y) : "memory"); }
#define EL "{ .reg .pred p; elect.sync _|p, 0xffffffff;\n @p "
__device__ __forceinline__ void e_init(uint32_t bar, uint32_t cnt) { asm volatile(EL "mbarrier.init.shared::cta.b64 [%0], %1; }" :: "r"(bar), "r"(cnt) : "memory"); }
__device__ __forceinline__ void e_expect(uint32_t bar, uint32_t bytes) { asm volatile(EL "mbarrier.arrive.expect_tx.shared::cta.b64 _, [%0], %1; }" :: "r"(bar), "r"(bytes) : "memory"); }
__device__ __forceinline__ void e_arrive(uint32_t bar, uint32_t n) { asm volatile(EL "mbarrier.arrive.shared::cta.b64 _, [%0], %1; }" :: "r"(bar), "r"(n) : "memory"); }
__device__ __forceinline__ void e_arrive_rem(uint32_t bar, uint32_t n) { asm volatile(EL "mbarrier.arrive.shared::cluster.b64 _, [%0], %1; }" :: "r"(bar), "r"(n) : "memory"); }
__device__ __forceinline__ void tma2(uint32_t dst, const CUtensorMap* m, uint32_t bar, int a, int b) {
    asm volatile(EL "cp.async.bulk.tensor.2d.shared::cluster.global.mbarrier::complete_tx::bytes [%0], [%1, {%3, %4}], [%2]; }" :: "r"(dst), "l"(m), "r"(bar), "r"(a), "r"(b) : "memory"); }
__device__ __forceinline__ void tma3(uint32_t dst, const CUtensorMap* m, uint32_t bar, int a, int b, int c) {
    asm volatile(EL "cp.async.bulk.tensor.3d.shared::cluster.global.mbarrier::complete_tx::bytes [%0], [%1, {%3, %4, %5}], [%2]; }" :: "r"(dst), "l"(m), "r"(bar), "r"(a), "r"(b), "r"(c) : "memory"); }
__device__ __forceinline__ void tma4(uint32_t dst, const CUtensorMap* m, uint32_t bar, int a, int d) {
    asm volatile(EL "cp.async.bulk.tensor.4d.shared::cluster.global.mbarrier::complete_tx::bytes [%0], [%1, {%3, %5, %5, %4}], [%2]; }" :: "r"(dst), "l"(m), "r"(bar), "r"(a), "r"(d), "r"(0) : "memory"); }
__device__ __forceinline__ void tma5(uint32_t dst, const CUtensorMap* m, uint32_t bar, int a, int e) {
    asm volatile(EL "cp.async.bulk.tensor.5d.shared::cluster.global.mbarrier::complete_tx::bytes [%0], [%1, {%3, %5, %5, %5, %4}], [%2]; }" :: "r"(dst), "l"(m), "r"(bar), "r"(a), "r"(e), "r"(0) : "memory"); }
__device__ __forceinline__ void bulk_g2s(uint32_t dst, const void* src, uint32_t bar, uint32_t bytes) {
    asm volatile(EL "cp.async.bulk.shared::cluster.global.mbarrier::complete_tx::bytes [%0], [%1], %3, [%2]; }" :: "r"(dst), "l"(src), "r"(bar), "r"(bytes) : "memory"); }
__device__ __forceinline__ void bulk_s2s(uint32_t dst, uint32_t src, uint32_t bar, uint32_t bytes) {
    asm volatile(EL "cp.async.bulk.shared::cluster.shared::cta.mbarrier::complete_tx::bytes [%0], [%1], %3, [%2]; }" :: "r"(dst), "r"(src), "r"(bar), "r"(bytes) : "memory"); }
__device__ __forceinline__ void bulk_s2g(void* dst, uint32_t src, uint32_t bytes) {
    asm volatile(EL "cp.async.bulk.global.shared::cta.bulk_group [%0], [%1], %2; }" :: "l"(dst), "r"(src), "r"(bytes) : "memory"); }
__device__ __forceinline__ void bulk_red(void* dst, uint32_t src, uint32_t bytes) {
    asm volatile(EL "cp.reduce.async.bulk.global.shared::cta.bulk_group.add.f32 [%0], [%1], %2; }" :: "l"(dst), "r"(src), "r"(bytes) : "memory"); }
__device__ __forceinline__ void bulk_finish(uint32_t bar, uint32_t n) {
    asm volatile("cp.async.bulk.commit_group;\n cp.async.bulk.wait_group 0;\n fence.proxy.async.global;" ::: "memory");
    e_arrive(bar, n);
}
__device__ __forceinline__ void pf_l2(const uint8_t* p) { asm volatile(EL "cp.async.bulk.prefetch.L2.global [%0], 10368; }" :: "l"(p) : "memory"); }
__device__ __forceinline__ void pf_map(const CUtensorMap* m) { asm volatile(EL "prefetch.tensormap [%0]; }" :: "l"(m) : "memory"); }
__device__ __forceinline__ void poll_ge(const unsigned* p, unsigned target) {
    for (;;) {
        unsigned v; asm volatile("ld.acquire.gpu.global.u32 %0, [%1];" : "=r"(v) : "l"(p) : "memory");
        if (__all_sync(0xffffffffu, (int)(v - target) >= 0)) break;
    }
}
__device__ __forceinline__ void signal_cnt(unsigned* p) { asm volatile(EL "red.release.gpu.global.add.u32 [%0], 1; }" :: "l"(p) : "memory"); }
__device__ __forceinline__ uint32_t read_epoch(uint32_t bb) {
    uint32_t e;
    asm volatile("ld.relaxed.gpu.global.u32 %0, [%1];" : "=r"(e) : "l"(&g_epoch) : "memory");
    asm volatile("st.shared.v2.u32 [%0], {%1, %2};" :: "r"(bb + EPOVAL), "r"(e), "r"(0xff800000u) : "memory");
    __syncwarp();
    e_arrive(bb + EPO, 1);
    return e;
}
__device__ __forceinline__ uint32_t get_epoch(uint32_t bb) { mb_wait(bb + EPO, 0); uint32_t e; asm volatile("ld.shared.u32 %0, [%1];" : "=r"(e) : "r"(bb + EPOVAL) : "memory"); return e; }

template <int O, int L> __device__ __forceinline__ float softmax_row(const float (&a)[L], uint32_t (&pp)[9], uint32_t (&pn)[9], float lo) {
    float mx = fmaxf(a[O], a[O + 1]), mn = fminf(a[O], a[O + 1]);
    mx = fmaxf(mx, lo); mn = fminf(mn, -lo);
#pragma unroll
    for (int j = 1; j < 9; j++) {
        if (O) { mx = fmaxf(fmaxf(mx, a[O + 4 * j]), a[O + 4 * j + 1]); mn = fminf(fminf(mn, a[O + 4 * j]), a[O + 4 * j + 1]); }
        else { mx = fmaxf(mx, fmaxf(a[O + 4 * j], a[O + 4 * j + 1])); mn = fminf(mn, fminf(a[O + 4 * j], a[O + 4 * j + 1])); }
    }
    float ep[18], en[18];
#pragma unroll
    for (int j = 0; j < 9; j++) {
        ep[2 * j] = ex2f(a[O + 4 * j] - mx); ep[2 * j + 1] = ex2f(a[O + 4 * j + 1] - mx);
        en[2 * j] = ex2f(mn - a[O + 4 * j]); en[2 * j + 1] = ex2f(mn - a[O + 4 * j + 1]);
    }
    float s0 = ep[0], s1 = ep[1], t0 = en[0], t1 = en[1];
#pragma unroll
    for (int j = 1; j < 9; j++) { s0 += ep[2 * j]; s1 += ep[2 * j + 1]; t0 += en[2 * j]; t1 += en[2 * j + 1]; }
    const float rp = rcpf(s0 + s1), rn = rcpf(t0 + t1);
#pragma unroll
    for (int j = 0; j < 9; j++) { pp[j] = pack2(ep[2 * j] * rp, ep[2 * j + 1] * rp); pn[j] = pack2(en[2 * j] * rn, en[2 * j + 1] * rn); }
    return fminf(ep[0], lo);
}

struct cf { float x, y; };
__device__ __forceinline__ cf cmul(cf a, cf b) { return {fmaf(a.x, b.x, -a.y * b.y), fmaf(a.x, b.y, a.y * b.x)}; }
__device__ __forceinline__ cf csq(cf a) { return {fmaf(a.x, a.x, -a.y * a.y), 2.f * a.x * a.y}; }
__device__ __forceinline__ cf cfma(cf a, cf b, cf c) { return {fmaf(a.x, b.x, fmaf(-a.y, b.y, c.x)), fmaf(a.x, b.y, fmaf(a.y, b.x, c.y))}; }
__device__ __forceinline__ cf csel(bool p, cf a, cf b) { return {p ? a.x : b.x, p ? a.y : b.y}; }
__device__ __forceinline__ float bf2f(unsigned short h) { return __uint_as_float((uint32_t)h << 16); }

__device__ __forceinline__ void cta_sync() { asm volatile("bar.sync 14, 512;" ::: "memory"); cl_arrive(); }
__device__ __forceinline__ void a_producer(const Params& P, uint32_t sb, int pw, int c, int tile) {
    const uint32_t bb = sb + BAR;
    if (pw < 2) {
        int slot = pw + 3; uint32_t par = 1;
        const int a0 = c ? 25 : 18, a1 = c ? 23 : 20, tc = c ? 1440 : 1408;
        const CUtensorMap* mt = &P.m[2 + c];
#pragma unroll 1
        for (int it = pw; it < 18; it += 2) {
            const uint32_t bar = bb + R1(slot), dst = sb + slot * 20480;
            const bool wx = pw == 0 && it < 8;
            mb_wait(bar + 8, par);
            e_expect(bar, wx ? 20480 + 8192 : 20480);
            if (wx) tma2(sb + A_X + it * 4096, &P.m[0], bar, it * 32, tile * 64);
            tma3(dst, &P.m[1], bar, 0, it * 32, a0);
            tma3(dst + 8192, &P.m[1], bar, 0, it * 32, a1);
            tma2(dst + 16384, mt, bar, tc, it * 32);
            if (it == 0) cta_sync();
            if (it == 5) {
                e_expect(bb + AXF(0), 2 * 8192); e_expect(bb + AXF(1), 3 * 8192);
#pragma unroll 1
                for (int k = 4; k < 9; k++) tma2(sb + A_X + k * 8192, &P.m[0], bb + AXF(k > 5), k * 64, tile * 64);
            }
            slot += 2; if (slot >= 7) { slot -= 7; par ^= 1; }
        }
        if (pw) {
#pragma unroll 1
            for (int i = 0; i < 3; i++) { mb_wait(bb + KRD(i), 0); signal_cnt(&g_cnt[(CNT_KV + 4 * c + (i ^ (2 * c))) * 32]); }
            return;
        }
        const uint8_t* src = (const uint8_t*)g_wimg + (size_t)(c * 54) * 18432;
        par = 1;
#pragma unroll 1
        for (int r = 0; r < 9; r++) {
            if (r == 0 || r == 3) { mb_wait(bb + RDY(r & 1), 0); proxy_fence_g(); }
#pragma unroll 1
            for (int s = 0; s < 6; s++) {
                const uint32_t bar = bb + R2(s);
                mb_wait(r ? bar + 8 : bb + R1(s) + 8, r ? par : 0);
                if (r == 5 && s == 2) mb_wait(bb + KRD(1), 0);
                e_expect(bar, 18432); bulk_g2s(sb + s * 18432, src, bar, 18432); src += 18432;
                if (r == 6 && s == 1) { e_arrive(bb + XD(0), 8); e_arrive_rem((bb ^ 0x1000000u) + XD(0), 8); }
            }
            par ^= 1;
        }
    } else if (pw == 2) {
        const int lane = threadIdx.x & 31;
        const unsigned e = read_epoch(bb) + 1;
        poll_ge(&g_cnt[(CNT_K + 2 * c) * 32], 16 * e);
        e_arrive(bb + RDY(0), 1); PSTP(1);
        poll_ge(&g_cnt[(lane & 1 ? CNT_WO + c : CNT_K + 2 * c + 1) * 32], (lane & 1 ? 32 : 16) * e);
        e_arrive(bb + RDY(1), 1); PSTP(2);
#pragma unroll 1
        for (int tq = 0; tq < 4; tq++) { poll_ge(&g_cnt[(CNT_KV + 4 * c + (tq ^ (2 * c))) * 32], 32 * e); e_arrive(bb + KVR(tq), 1); PSTP(3 + tq); }
        if (blockIdx.x == 0) {
            poll_ge(&g_cnt[min(lane, 5) * 32], (lane < 4 ? 16 : 32) * e);
            asm volatile(EL "st.relaxed.gpu.global.u32 [%0], %1; }" :: "l"(&g_epoch), "r"(e) : "memory");
        }
    } else {
#pragma unroll
        for (int i = 0; i < 4; i++) e_expect(bb + PART(2 * i + 1), 9216);
        mb_wait_b(bb + EPO);
        uint32_t e; asm volatile("ld.shared.u32 %0, [%1];" : "=r"(e) : "r"(bb + EPOVAL) : "memory");
        mb_wait_b(bb + SIG(4)); signal_cnt(&g_cnt[(CNT_WO + c) * 32]); PSTP(7);
#pragma unroll 1
        for (int i = 0; i < 4; i++) {
            const int g4 = 4 * c + (i ^ (2 * c));
            mb_wait_b(bb + SIG(i));
            bulk_red(&g_kvacc[e & 1][g4 * 720], sb + A_ST0(i), 5760);
            bulk_red(&g_kvacc[e & 1][g4 * 720 + 360], sb + A_ST1(i), 5760);
            bulk_finish(bb + KRD(i), 4); PSTP(8 + i);
        }
        signal_cnt(&g_cnt[(CNT_KV + 4 * c + (3 ^ (2 * c))) * 32]);
    }
}

template <int NB, int L> __device__ __forceinline__ void v_mainloop(float (&acc)[L], uint32_t bb, uint32_t boff, int lane) {
    uint32_t par = 0, prev = bb + DUMMY, bar = bb + R1(3), alo = (SB0 + A_X) >> 4, blo = ((SB0 + boff + 3 * 20480) >> 4) | (256u << 16);
    reg_def(acc);
    mb_wait(bar, 0);
    PST(26);
#pragma unroll 1
    for (int kc = 0; kc < 9; kc++) {
        if (kc == 4 || kc == 6) mb_wait(bb + AXF(kc > 5), 0);
        if (kc == 2) PST(27);
        if (kc == 4) PST(28);
        if (kc == 6) PST(29);
#pragma unroll
        for (int h = 0; h < 2; h++) {
            uint32_t nbar = bar + 16, nblo = blo + 1280;
            if (nbar == bb + R1(7)) { nbar = bb; nblo -= 7 * 1280; par ^= 1; }
            const bool last = h == 1 && kc == 8;
            if (NB == 128) st_v128<0>(acc, alo + 4 * h, DHI_SW, blo, DHI_SW, h | kc, last ? bar : nbar, last ? 0 : par, prev, 0, 0, lane);
            else st_v160<0>(acc, alo + 4 * h, DHI_SW, blo, DHI_SW, h | kc, last ? bar : nbar, last ? 0 : par, prev, 0, 0, lane);
            prev = bar + 8; bar = nbar; blo = nblo;
        }
        alo += 512;
    }
    wg_wait<0>(); reg_fence(acc);
    if (lane == 0) mb_arrive(prev);
}

__device__ __forceinline__ void n144_mainloop(float (&acc)[72], uint32_t bb, int U, int lane) {
    uint32_t hi = (0xa >> U) & 1, par = (0x26 >> U) & 1, prev = bb + DUMMY;
    const bool oa = U >= 4;
    uint32_t alo = ((SB0 + A_X) >> 4) | (oa ? 64u << 16 : 0u);
    const uint32_t ahi = oa ? 8u : DHI_SW, ks = oa ? 128 : 2;
    if (oa) mb_wait(bb + PART(0), 0);
    mb_wait(bb + R2(3 * hi), par);
#pragma unroll 1
    for (int blk = 0; blk < 3; blk++) {
        const bool last = blk == 2 || (oa && blk == 1);
        const uint32_t bar = bb + R2(3 * hi), blo = ((SB0 >> 4) + hi * 3456) | (8u << 16);
        uint32_t xb = bb + (last ? TOK(U + (oa && blk == 2 ? 2 : 0)) : DUMMY);
        asm volatile("" : "+r"(xb));
#pragma unroll
        for (int h = 0; h < 3; h++) {
            const uint32_t nb = h < 2 ? bar + 16 * h + 16 : (last ? bar + 32 : bb + R2(3 - 3 * hi)), np = h < 2 || last ? par : par ^ hi;
            if (h == 1) st_n144<1>(acc, alo, ahi, blo + 1152 * h, 16, 1, nb, np, prev, xb, ks, lane); else st_n144<0>(acc, alo, ahi, blo + 1152 * h, 16, h | blk, nb, np, prev, 0, ks, lane);
            alo += 512; prev = bar + 16 * h + 8;
            if (oa && (h < 2 || !last)) mb_wait(bb + PART(min(3 * blk + h + 1, 7)), 0);
        }
        par ^= hi; hi ^= 1;
        if (oa && blk == 1) {
            wg_wait<0>();
            if (lane == 0) mb_arrive(prev);
            prev = bb + DUMMY; hi = U & 1; par = 0;
            PST(20);
            mb_wait(bb + TOK(U + 1), 0); mb_wait(bb + PART(6), 0); mb_wait(bb + R2(3 * hi), 0);
            PST(21);
        }
    }
    wg_wait<0>(); reg_fence(acc);
    if (lane == 0) mb_arrive(prev);
}
template <int O> __device__ __forceinline__ void a_store(const float (&acc)[72], float* op, int q) {
#pragma unroll
    for (int i = 0; i < 4; i++) {
        *(float4*)(op + 16 * i) = make_float4(acc[O + 8 * i], acc[O + 8 * i + 1], acc[O + 8 * i + 4], acc[O + 8 * i + 5]);
        *(float4*)(op + 8 * 1152 + 16 * i) = make_float4(acc[O + 8 * i + 2], acc[O + 8 * i + 3], acc[O + 8 * i + 6], acc[O + 8 * i + 7]);
    }
    *(float2*)(op + 64 - 2 * q) = make_float2(acc[O + 32], acc[O + 33]);
    *(float2*)(op + 8 * 1152 + 64 - 2 * q) = make_float2(acc[O + 34], acc[O + 35]);
}

template <int PR> __device__ __forceinline__ void kv_stage(const float (&kv)[36], uint32_t base, int w, int g, int q) {
#pragma unroll
    for (int r = 0; r < 2; r++) {
        const int R = 16 * w + g + 8 * r;
        int d = R - (PR ? 4 : 8) - 18 * (q >> 1);
        const bool one = R == (PR ? 40 : 0);
        const bool ok = one || (unsigned)d < 18u;
        if (one) d = 18;
        const uint32_t p = base + (q >> 1) * 2880 + d * 16 + (q & 1) * 8;
        if (ok) {
#pragma unroll
            for (int j = 0; j < 9; j++) sts64(p + j * 320, __float_as_uint(kv[4 * j + 2 * r]), __float_as_uint(kv[4 * j + 2 * r + 1]));
        }
    }
}
__device__ __forceinline__ void kv_mma(float (&kv)[36], float (&kw)[36], int g4) {
    wg_fence();
    const uint32_t alo = (((SB0 + A_AUX) >> 4) + g4 * 640) | (8u << 16), blo = ((SB0 + A_PHI) >> 4) | (8u << 16);
#pragma unroll
    for (int ks = 0; ks < 4; ks++) {
        wg72<1, 1, 0>(kv, alo + 16 * ks, 64, blo + 16 * ks, 64, ks);
        wg72<1, 1, 0>(kw, alo + 320 + 16 * ks, 64, blo + 580 + 16 * ks, 64, ks);
    }
    wg_commit();
}
__device__ __forceinline__ void o_write(const uint32_t (&o)[18], uint32_t sb, uint32_t rsb, int part, int wg, int w, int lane) {
    mb_wait(sb + BAR + XD(part >> 1), 0);
    const uint32_t base = sb + A_X + part * 18432;
    const uint32_t a = base + ((lane >> 4) << 10) + (2 * w + ((lane >> 3) & 1)) * 128 + (lane & 7) * 16;
#pragma unroll
    for (int jp = 0; jp < 4; jp++) stsm4(a + jp * 2048, o[4 * jp], o[4 * jp + 1], o[4 * jp + 2], o[4 * jp + 3]);
    stsm2(a + 8192, o[16], o[17]);
    proxy_fence();
    wg_bar(wg);
    if (w == 0) {
        bulk_s2s(rsb + A_X + part * 18432 + 9216, base, rsb + BAR + PART(2 * part + 1), 9216);
        e_arrive(sb + BAR + PART(2 * part), 1);
    }
}

__device__ __forceinline__ void bd_load(float (&kl)[24], uint32_t bb, uint32_t par, int c, int tq, int t) {
    mb_wait(bb + KVR(tq), 0);
    const float4* ks = &g_kvacc[par][(16 * c + 4 * (tq ^ (2 * c)) + ((t >> 1) & 3)) * 180 + (t & 1) + 2 * (t >> 3)];
#pragma unroll
    for (int i = 0; i < 6; i++)
        asm volatile("ld.relaxed.gpu.global.v4.f32 {%0, %1, %2, %3}, [%4];" : "=f"(kl[4 * i]), "=f"(kl[4 * i + 1]), "=f"(kl[4 * i + 2]), "=f"(kl[4 * i + 3])
                     : "l"(ks + (i < 5 || t < 80 ? 32 * i : 0)) : "memory");
}
__device__ __forceinline__ void bd_store(const float (&kl)[24], uint32_t sb, int tq, int t) {
    mb_wait(sb + BAR + (tq & 2 ? NUMD(tq & 1) : KRD(2 + tq)), 0);
    if (tq == 0) mb_wait(sb + BAR + KVD(3), 0);
    const int hq = (t >> 1) & 3;
#pragma unroll
    for (int i = 0; i < 6; i++) {
        const int cb = 16 * i + (t >> 3), b = (cb * 205) >> 11;
        if (i < 5 || t < 80) {
            const uint32_t a = sb + A_AUX + (tq & 1) * 23040 + cb * 128 + b * 1280 + (t & 7) * 16, vp = pack2(kl[4 * i], kl[4 * i + 1]), vn = pack2(kl[4 * i + 2], kl[4 * i + 3]);
            sts128(a, hq == 0 ? vp : 0, hq == 1 ? vp : 0, hq == 2 ? vp : 0, hq == 3 ? vp : 0);
            sts128(a + 1280, hq == 0 ? vn : 0, hq == 1 ? vn : 0, hq == 2 ? vn : 0, hq == 3 ? vn : 0);
        }
    }
    proxy_fence();
}
__device__ __forceinline__ void a_consumer(const Params& P, uint32_t sb, int warp, int c, int tile) {
    const uint32_t bb = sb + BAR, rsb = sb ^ 0x1000000u, rb = rsb + BAR;
    const int wg = warp >> 2, w = warp & 3, lane = threadIdx.x & 31, g = lane >> 2, q = lane & 3, t = threadIdx.x & 127;
    const bool lead = lane == 0;
    const uint32_t la = sb + A_AUX + (2 * w + ((lane >> 3) & 1)) * 128 + (lane & 7) * 16 + 1024;
    const int jj = lane >> 4;
    float acc[72];
    uint32_t vh[36];
#pragma unroll
    for (int i = 0; i < 36; i++) asm volatile("{ .reg .b32 t; mov.b32 %0, t; }" : "=r"(vh[i]));
    cta_sync();
    PST(0);
    if (wg == 2) {
#pragma unroll 1
        for (int i = 0; i < 3; i++) {
            const int tt = t + 128 * i;
            if (tt < 324) {
                const int U = tile * 324 + tt, s = U / 288, rem = U - s * 288;
                int kb, col;
                const int half = (rem >> 2) & 1, qq = rem & 3;
                const int sl = rem / 72, ng = (rem - 72 * sl) >> 3;
                const int tb = s < 24 ? s >= 12 : s >= 30;
                kb = 4 * (s - (s < 24 ? 12 * tb : 12 + 6 * tb)) + (sl & 2) + half; col = 72 * (sl & 1) + 144 * tb;
                col += ng < 8 ? 16 * (ng >> 1) + 4 * qq + 2 * (ng & 1) : 64 + 2 * qq;
                const int part = kb / 18, r = kb - 18 * part, peer = r >= 9, jj = r - 9 * peer, own = c ^ peer;
                const int h0 = 16 * own + 4 * (part ^ (2 * own));
                const uint32_t* src = P.wo + (18 * h0 + 2 * jj) * 288 + ((288 * c + col) >> 1);
                uint32_t v[8];
#pragma unroll
                for (int k = 0; k < 8; k++) v[k] = __ldg(src + ((k >> 1) * 18 + (k & 1)) * 288);
                uint4* dst = g_wimg + (size_t)(c * 108 + 72) * 576 + U * 2;
                dst[0] = make_uint4(__byte_perm(v[0], v[1], 0x5410), __byte_perm(v[2], v[3], 0x5410), __byte_perm(v[4], v[5], 0x5410), __byte_perm(v[6], v[7], 0x5410));
                dst[1] = make_uint4(__byte_perm(v[0], v[1], 0x7632), __byte_perm(v[2], v[3], 0x7632), __byte_perm(v[4], v[5], 0x7632), __byte_perm(v[6], v[7], 0x7632));
            }
        }
        __syncwarp();
        if (lead) mb_arrive(bb + SIG(4));
        const uint32_t e = get_epoch(bb);
        if (t < 90) g_kvacc[(e & 1) ^ 1][blockIdx.x * 90 + t] = make_float4(0.f, 0.f, 0.f, 0.f);
        cl_wait();
        PST(1);
    } else {
        cl_wait();
        if (wg == 0) {
            float av[64];
            v_mainloop<128>(av, bb, 0, lane);
            PST(1);
            mb_wait(bb + R1(6) + 8, 0);
#pragma unroll
            for (int jp = 0; jp < 8; jp++) {
                const int b = 2 * jp + 2 * c + jj;
                stsm4(la + (b + (b >= 9)) * 1024, pack2(av[8 * jp], av[8 * jp + 1]), pack2(av[8 * jp + 2], av[8 * jp + 3]), pack2(av[8 * jp + 4], av[8 * jp + 5]), pack2(av[8 * jp + 6], av[8 * jp + 7]));
            }
        } else {
            float av[80];
            v_mainloop<160>(av, bb, 8192, lane);
            PST(1);
            uint32_t pk[40];
#pragma unroll
            for (int i = 0; i < 40; i++) pk[i] = pack2(av[2 * i], av[2 * i + 1]);
            mb_wait(bb + R1(6) + 8, 0);
            stsm4(la + (c ? jj : 17 + jj) * 1024, c ? pk[28] : pk[0], c ? pk[29] : pk[1], c ? pk[30] : pk[2], c ? pk[31] : pk[3]);
            sts128(sb + A_AUX + (t >> 6) * 10240 + (t & 63) * 16, 0x3f803f80u, 0x3f803f80u, 0x3f803f80u, 0x3f803f80u);
            if (t < 64) sts128(sb + A_AUX + 20480 + t * 16, 0x3f803f80u, 0x3f803f80u, 0x3f803f80u, 0x3f803f80u);
#pragma unroll
            for (int i = 0; i < 36; i++) vh[i] = i < 28 && c ? pk[i] : pk[i + 4];
        }
        proxy_fence(); __syncwarp();
        if (lead) mb_arrive(bb + VST);
        PST(2);
    }
    const uint32_t par = get_epoch(bb) & 1;
    int U = wg == 2 ? 0 : wg + 1;
#pragma unroll 1
    for (;;) {
        if (U) mb_wait(bb + TOK(U - 1), 0);
        PST(pb);
        reg_def(acc);
        n144_mainloop(acc, bb, U, lane);
        PST(pb + 1);
        if (U >= 4) break;
        if (U == 3 && lead) { mb_arrive_n(bb + XD(1), 2); mb_arrive_rem(rb + XD(1), 2); }
        if (U == 2) {
            mb_wait(bb + KVD(1), 0); mb_wait(bb + KRD(0), 0);
#pragma unroll
            for (int i = 0; i < 9; i++) {
                const int b = (c ? (i < 7 ? 2 * i + 4 : 2 * i - 14) : 2 * i) + jj;
                stsm4(la + (b + (b >= 9)) * 1024, vh[4 * i], vh[4 * i + 1], vh[4 * i + 2], vh[4 * i + 3]);
            }
            proxy_fence(); __syncwarp();
            if (lead) mb_arrive_n(bb + VST, 2);
        }
        int G = U < 2 ? U : U + 2;
#pragma unroll 1
        for (;;) {
            const int tq = G - 4;
            float kl[24];
            const bool own = G == 4 || G == 7;
            if (G == 7) { bd_load(kl, bb, par, c, 3, t); PST(pb + 2); } else reg_def(kl);
            float lo;
            asm volatile("ld.volatile.shared.f32 %0, [%1];" : "=f"(lo) : "r"(bb + EPOVAL + 4) : "memory");
            uint32_t p0[9], n0[9], p1[9], n1[9];
            softmax_row<2>(acc, p1, n1, softmax_row<0>(acc, p0, n0, lo));
            PST(pb + 3);
            if (G < 4) {
                const uint32_t pa = sb + A_PHI + (q >> 1) * 9280 + 2 * w * 128 + g * 16 + (q & 1) * 8;
                mb_wait(bb + (G ? KVD(G - 1) : VST), 0);
#pragma unroll
                for (int j = 0; j < 9; j++) { sts64(pa + j * 1024, p0[j], n0[j]); sts64(pa + j * 1024 + 128, p1[j], n1[j]); }
                proxy_fence();
                if (G == 2) mb_wait(bb + VST, 1);
                wg_bar(wg);
                PST(pb + 4);
                float kv[36], kw[36];
                kv_mma(kv, kw, G & 1);
                wg_wait<0>(); reg_fence(kv); reg_fence(kw);
                if (lead) mb_arrive(bb + KVD(G));
                mb_wait(bb + KVD(G), 0);
                if (G == 1) mb_wait(bb + TOK(2), 0);
                if (G & 1) mb_wait(bb + (G == 1 ? R2(2) + 8 : KRD(2)), 0);
                PST(pb + 5);
                if (w < 3) { kv_stage<0>(kv, sb + A_ST0(G), w, g, q); kv_stage<1>(kw, sb + A_ST1(G), w, g, q); }
                proxy_fence(); __syncwarp();
                if (lead) mb_arrive(bb + SIG(G));
                PST(pb + 6);
            } else {
                const uint32_t so = A_AUX + (tq & 1) * 23040;
                if (G == 4) bd_load(kl, bb, par, c, 0, t);
                if (own) { bd_store(kl, sb, tq, t); wg_bar(wg); } else mb_wait(bb + BD(tq), 0);
                PST(pb + 4);
                float nm[40];
                wg_fence();
                const uint32_t blo = ((SB0 + so) >> 4) | (80u << 16);
#pragma unroll
                for (int b = 0; b < 9; b++) wgrs80(nm, p0[b], p1[b], n0[b], n1[b], blo + 160 * b, 8, b);
                wg_commit();
                wg_wait<0>(); reg_fence(nm);
                if (tq < 2 && lead) mb_arrive(bb + NUMD(tq));
                uint32_t o[18];
                const float i0 = rcpf(nm[36] + 1e-6f), i1 = rcpf(nm[38] + 1e-6f);
#pragma unroll
                for (int j = 0; j < 9; j++) { o[2 * j] = pack2(nm[4 * j] * i0, nm[4 * j + 1] * i0); o[2 * j + 1] = pack2(nm[4 * j + 2] * i1, nm[4 * j + 3] * i1); }
                PST(pb + 5);
                o_write(o, sb, rsb, tq, wg, w, lane);
                PST(pb + 6);
            }
            if (G & 2) break;
#pragma unroll
            for (int i = 0; i < 36; i++) acc[i] = acc[36 + i];
            G += 2;
        }
        if (U == 3) { cl_arrive(); return; }
        if (U == 1) {
#pragma unroll 1
            for (int tq = 1; tq < 3; tq++) {
                float kl[24];
                bd_load(kl, bb, par, c, tq, t); bd_store(kl, sb, tq, t);
                __syncwarp();
                if (lead) mb_arrive(bb + BD(tq));
                PST(14 + tq);
            }
        }
        U += 3;
#pragma unroll
        for (int i = 0; i < 36; i++) asm volatile("{ .reg .b32 t; mov.b32 %0, t; }" : "=r"(vh[i]));
    }
    cl_arrive();
    float* op = P.out + (size_t)(64 * tile + 16 * w + g) * 1152 + 288 * c + 4 * q + (wg == 1 ? 144 : 0);
    a_store<0>(acc, op, q);
    a_store<36>(acc, op + 72, q);
    PST(31);
}

__device__ __forceinline__ void b_producer(const Params& P, uint32_t sb, int pw, int c, int tile) {
    const uint32_t bb = sb + BAR;
    const int mtx = tile >> 4, G8 = (tile >> 1) & 7, rq = 2 * (tile & 1) + c;
    if (pw < 2) {
        if (pw == 0) {
            e_expect(bb + FLD, 20736 + 2592);
            tma2(sb + B_HD, &P.m[10], bb + FLD, (mtx ? 0 : 576) + 72 * G8, 144 * rq);
            bulk_g2s(sb + B_HD + 20736, P.wphi + G8 * 2592, bb + FLD, 2592);
        }
        int slot = pw + 3, kc = pw, m0 = c ? 40 : 0; uint32_t par = 1;
#pragma unroll 1
        for (int it = pw; it < 57; it += 2) {
            const uint32_t bar = bb + R1(slot), dst = sb + slot * 24576;
            mb_wait(bar + 8, par);
            e_expect(bar, it < 5 ? 24576 + 8192 : 24576);
            if (it < 27) {
                if (it < 5) tma5(sb + B_X + it * 8192, &P.m[4], bar, kc * 64, tile);
                tma4(dst, &P.m[5], bar, kc * 64, m0);
                tma4(dst + 8192, &P.m[5], bar, kc * 64, m0 + 4);
                tma4(dst + 16384, &P.m[5], bar, kc * 64, m0 == 64 ? 36 : m0 + 8);
                if (it == 0) cta_sync();
                if (it == 3) {
                    e_expect(bb + BXF, 4 * 8192);
#pragma unroll 1
                    for (int k = 5; k < 9; k++) tma5(sb + B_X + k * 8192, &P.m[4], bb + BXF, k * 64, tile);
                }
                if (it == 24) { mb_wait(bb + FRD, 0); e_arrive(bb + BXD, 1); }
                kc += 2; if (kc >= 9) { kc -= 9; m0 += 12; }
            } else {
                const uint32_t e = P.b2[c][it - 27];
                const int k0 = (int)(e >> 16) - 32;
                tma5(dst, &P.m[6 + c + (e & 2)], bar, k0, (e >> 4) & 63);
                tma5(dst + 12288, &P.m[6 + c + ((e >> 1) & 2)], bar, k0, (e >> 10) & 63);
            }
            slot += 2; if (slot >= 5) { slot -= 5; par ^= 1; }
        }
    } else if (pw == 2) {
        read_epoch(bb);
        mb_wait(bb + TOK(0), 0);
        pf_l2(P.cw[0] + (2 * tile + c) * 10368); pf_l2(P.cw[1] + (2 * tile + c) * 10368);
    } else {
#pragma unroll
        for (int i = 0; i < 3; i++) e_expect(bb + RFULL(i), 12288);
        mb_wait_b(bb + EPO);
        mb_wait_b(bb + FSIG);
        const int cc = G8 >> 2;
        e_arrive(bb + FRD, 1); signal_cnt(&g_cnt[(CNT_K + 2 * cc + mtx) * 32]); PSTP(1);
    }
}

__device__ __forceinline__ void mma16(float (&d)[4], uint32_t a0, uint32_t a1, uint32_t a2, uint32_t a3, uint32_t b0, uint32_t b1) {
    asm("mma.sync.aligned.m16n8k16.row.col.f32.bf16.bf16.f32 {%0,%1,%2,%3}, {%4,%5,%6,%7}, {%8,%9}, {%0,%1,%2,%3};"
        : "+f"(d[0]), "+f"(d[1]), "+f"(d[2]), "+f"(d[3]) : "r"(a0), "r"(a1), "r"(a2), "r"(a3), "r"(b0), "r"(b1));
}
__device__ __forceinline__ void mma8(float (&d)[4], uint32_t a0, uint32_t a1, uint32_t b0) {
    asm("mma.sync.aligned.m16n8k8.row.col.f32.bf16.bf16.f32 {%0,%1,%2,%3}, {%4,%5}, {%6}, {%0,%1,%2,%3};"
        : "+f"(d[0]), "+f"(d[1]), "+f"(d[2]), "+f"(d[3]) : "r"(a0), "r"(a1), "r"(b0));
}

__device__ __forceinline__ void agg_ld(uint32_t (&v)[3], const uint8_t* p, const uint8_t* p2, uint32_t& miss) {
    asm volatile("{ .reg .pred p; .reg .b32 m; min.u32 m, %0, %1; min.u32 m, m, %2; setp.eq.u32 p, m, 0;\n"
                 "@p ld.relaxed.gpu.global.v2.b32 {%0, %1}, [%4]; @p ld.relaxed.gpu.global.b32 %2, [%5]; @p mov.u32 %3, 1; }"
                 : "+r"(v[0]), "+r"(v[1]), "+r"(v[2]), "+r"(miss) : "l"(p), "l"(p2) : "memory");
}
template <int O> __device__ __forceinline__ uint32_t scan_pass1(float (&a)[96], cf& l, cf k, int q, int swap, cf& l16, cf& excl) {
    cf h = {a[O], a[O + 2]};
#pragma unroll
    for (int i = 1; i < 16; i++) h = cfma(l, h, {a[O + 4 * (i >> 1) + (i & 1)], a[O + 4 * (i >> 1) + 2 + (i & 1)]});
    l16 = csq(csq(csq(csq(l))));
    cf y = {__shfl_up_sync(0xffffffffu, h.x, 1, 4), __shfl_up_sync(0xffffffffu, h.y, 1, 4)};
    if (q >= 1) h = cfma(l16, y, h);
    y = {__shfl_up_sync(0xffffffffu, h.x, 2, 4), __shfl_up_sync(0xffffffffu, h.y, 2, 4)};
    if (q >= 2) h = cfma(csq(l16), y, h);
    const float ka = swap ? -k.y : k.x, kb = swap ? k.x : -k.y, kc = swap ? -k.x : -k.y, kd = swap ? -k.y : -k.x;
    h = {fmaf(ka, h.x, kb * h.y), fmaf(kc, h.x, kd * h.y)};
    excl = h;
    if (!swap) { l.y = -l.y; l16.y = -l16.y; }
    const uint32_t r = pack2(h.x, h.y);
    return r ? r : 0x8000u;
}
template <int O> __device__ __forceinline__ void scan_scale(float (&a)[96], cf k, int swap) {
    const float ka = swap ? -k.y : k.x, kb = swap ? k.x : -k.y, kc = swap ? -k.x : -k.y, kd = swap ? -k.y : -k.x;
#pragma unroll
    for (int i = 0; i < 16; i++) {
        const int ip = O + 4 * (i >> 1) + (i & 1);
        asm volatile("{ .reg .f32 a, b; mul.f32 a, %3, %1; mul.f32 b, %5, %1; fma.rn.f32 %1, %4, %0, b; fma.rn.f32 %0, %2, %0, a; }"
                     : "+f"(a[ip]), "+f"(a[ip + 2]) : "f"(ka), "f"(kb), "f"(kc), "f"(kd));
    }
}
template <int M> __device__ __forceinline__ void scan_pass2(const float (&a)[96], cf l, cf l16, const uint32_t (&v)[8][3], cf excl, int q, uint32_t h0a, uint32_t h1a, uint32_t io) {
    const cf l32 = csq(l16), l64 = csq(l32), l128 = csq(l64), l256 = csq(l128), one = {1.f, 0.f};
    cf cr = {__uint_as_float(v[7][M] << 16), __uint_as_float(v[7][M] & 0xffff0000u)};
#pragma unroll
    for (int i = 6; i >= 0; i--) cr = cfma(l256, cr, {__uint_as_float(v[i][M] << 16), __uint_as_float(v[i][M] & 0xffff0000u)});
    cr = cmul(cr, cmul(csel(q & 1, l64, one), csel(q & 2, l128, one)));
    cr.x += __shfl_xor_sync(0xffffffffu, cr.x, 1); cr.y += __shfl_xor_sync(0xffffffffu, cr.y, 1);
    cr.x += __shfl_xor_sync(0xffffffffu, cr.x, 2); cr.y += __shfl_xor_sync(0xffffffffu, cr.y, 2);
    cf h = cfma(cmul(csel(q & 1, l16, one), csel(q & 2, l32, one)), cr, excl);
    uint32_t re[8], im[8];
#pragma unroll
    for (int j = 0; j < 8; j++) {
        const cf h0 = cfma(l, h, {a[32 * M + 4 * j], a[32 * M + 4 * j + 2]});
        h = cfma(l, h0, {a[32 * M + 4 * j + 1], a[32 * M + 4 * j + 3]});
        re[j] = pack2(h0.x, h.x); im[j] = pack2(h0.y, h.y);
    }
    sts128(h0a, re[0], re[1], re[2], re[3]); sts128(h1a, re[4], re[5], re[6], re[7]);
    sts128(h0a + io, im[0], im[1], im[2], im[3]); sts128(h1a + io, im[4], im[5], im[6], im[7]);
}
__device__ __forceinline__ void b_load_xd(uint32_t (&u)[24], const Params& P, int row, int col) {
    const uint2* xp = P.xb + row * 144 + (col >> 2); const uint2* dp = P.dsk + (col >> 2);
#pragma unroll
    for (int i = 0; i < 6; i++) {
        const uint2 d = __ldg(dp + 4 * i);
#pragma unroll
        for (int r = 0; r < 2; r++) {
            const uint2 x = __ldg(xp + r * 8 * 144 + 4 * i);
            asm("mul.rn.bf16x2 %0, %1, %2;" : "=r"(u[4 * i + r]) : "r"(x.x), "r"(d.x)); asm("mul.rn.bf16x2 %0, %1, %2;" : "=r"(u[4 * i + 2 + r]) : "r"(x.y), "r"(d.y));
        }
    }
}
template <int O, int L> __device__ __forceinline__ void b_init_xd(float (&a)[L], const uint32_t (&u)[24]) {
#pragma unroll
    for (int i = 0; i < 24; i++) { a[O + 2 * i] = __uint_as_float(u[i] << 16); a[O + 2 * i + 1] = __uint_as_float(u[i] & 0xffff0000u); }
}
template <int O, int L> __device__ __forceinline__ void b_out(const float (&a)[L], uint32_t sb, int wg, int t, float* op) {
    mb_wait_cl(sb + BAR + RFULL(wg), 0);
    cl_arrive();
    PST(13);
    uint32_t r[24];
#pragma unroll
    for (int i = 0; i < 6; i++) asm volatile("ld.shared.v4.b32 {%0, %1, %2, %3}, [%4];" : "=r"(r[4 * i]), "=r"(r[4 * i + 1]), "=r"(r[4 * i + 2]), "=r"(r[4 * i + 3]) : "r"(sb + B_RECV + (wg & 1) * 12288 + t * 16 + i * 2048) : "memory");
    __syncwarp();
    if (wg == 0 && (t & 31) == 0) mb_arrive_rem((sb ^ 0x1000000u) + BAR + RFREE(1), 2);
#pragma unroll
    for (int i = 0; i < 12; i++) {
        const int o = 8 * (i >> 1) + 2 * (i & 1);
        const uint32_t u = r[o >> 1], v = r[(o >> 1) + 2];
        *(float4*)(op + (i & 1) * 8 * 1152 + 16 * (i >> 1)) = make_float4(a[O + o] + __uint_as_float(u << 16), a[O + 1 + o] + __uint_as_float(u & 0xffff0000u),
                                                                         a[O + 4 + o] + __uint_as_float(v << 16), a[O + 5 + o] + __uint_as_float(v & 0xffff0000u));
    }
    PST(14);
}
template <int I0, int I1, int L> __device__ __forceinline__ void b_send(const float (&a)[L], uint32_t rsb, int i3, int t) {
    const uint32_t dst = rsb + B_RECV + (i3 & 1) * 12288 + t * 16, bar = rsb + BAR + RFULL(i3);
#pragma unroll
    for (int i = I0; i < I1; i++) {
        asm volatile("st.async.weak.shared::cluster.mbarrier::complete_tx::bytes.v4.b32 [%0], {%1, %2, %3, %4}, [%5];"
            :: "r"(dst + i * 2048), "r"(pack2(a[8 * i], a[8 * i + 1])), "r"(pack2(a[8 * i + 2], a[8 * i + 3])), "r"(pack2(a[8 * i + 4], a[8 * i + 5])), "r"(pack2(a[8 * i + 6], a[8 * i + 7])), "r"(bar) : "memory");
    }
}
template <int U0, int U1> __device__ __forceinline__ void b2_run(float (&acc)[96], uint32_t bb, uint32_t s, uint32_t par, uint32_t tok, uint32_t& prev, int lane) {
    prev = bb + DUMMY;
    mb_wait(bb + R1(s), par);
#pragma unroll 1
    for (int u = U0; u < U1; u++) {
        const bool wrap = s == 4, last = u == 5;
        const uint32_t ns = wrap ? 0 : s + 1, np = par ^ wrap;
        uint32_t xb = bb + (u == 4 ? tok : DUMMY);
        asm volatile("" : "+r"(xb));
        st_b2d<U0 == 0>(acc, ((SB0 + B_HD) >> 4) + u * 512, DHI_SW, (SB0 >> 4) + s * 1536, DHI_SW, 1, bb + R1(last ? s : ns), last ? par : np, prev, xb, 0, lane);
        if (u == 1) mb_wait(bb + HR(1), 0);
        prev = bb + R1(s) + 8; s = ns; par = np;
    }
}
__device__ __forceinline__ void b_consumer(const Params& P, uint32_t sb, int warp, int c, int tile) {
    const uint32_t bb = sb + BAR, rsb = sb ^ 0x1000000u, rb = rsb + BAR;
    const int wg = warp >> 2, w = warp & 3, lane = threadIdx.x & 31, g = lane >> 2, q = lane & 3, t = threadIdx.x & 127;
    const bool lead = lane == 0;
    const int swap = P.swap;
    const int mq = 3 * wg + min(q, 2);
    const int sq = (c ? (mq < 8 ? 320 + 32 * mq : 288) : 32 * mq) + 8 * w + g;
    const unsigned short hre = __ldg(P.lre + sq), him = __ldg(P.lim + sq), hdt = __ldg(P.ldt + sq);
    cta_sync();
    PST(0);
    {
        const uint32_t wb = sb + B_HD + 20736 + w * 648 + 72 * q, ab = sb + B_HD + (48 * wg + g) * 144 + 36 * w + 4 * q;
        mb_wait(bb + FLD, 0);
        PST(16);
        uint32_t fb[3][3], fa[3][6];
#pragma unroll
        for (int nb = 0; nb < 3; nb++) {
            const uint32_t a = wb + 2 * (nb < 2 ? 8 * nb + g : 16 + (g & 1));
#pragma unroll
            for (int k = 0; k < 3; k++) {
                const uint32_t ak = k < 2 ? a + 288 * k : a - 72 * q + 576;
                unsigned short lo, hi;
                asm volatile("ld.shared.u16 %0, [%1];" : "=h"(lo) : "r"(ak)); asm volatile("ld.shared.u16 %0, [%1];" : "=h"(hi) : "r"(ak + 36));
                fb[nb][k] = k < 2 || q == 0 ? (uint32_t)lo | ((uint32_t)hi << 16) : 0u;
            }
        }
#pragma unroll
        for (int mt = 0; mt < 3; mt++)
#pragma unroll
            for (int i = 0; i < 6; i++) asm volatile("ld.shared.u32 %0, [%1];" : "=r"(fa[mt][i]) : "r"(ab + mt * 2304 + (i & 1) * 1152 + (i >> 1) * 16));
        asm volatile("bar.sync 13, 384;" ::: "memory");
        const int r8 = lane & 7, mh = (lane >> 3) & 1;
        const uint32_t ob = sb + B_HD + 3 * wg * 2304 + mh * 128 + (2 * w + (r8 & 1)) * 16, o4 = ob + ((lane >> 4) * 4 + (r8 >> 1)) * 256;
#pragma unroll
        for (int mt = 0; mt < 3; mt++) {
            uint32_t o[6];
#pragma unroll
            for (int nb = 0; nb < 3; nb++) {
                float d[4] = {0.f, 0.f, 0.f, 0.f};
                mma16(d, fa[mt][0], fa[mt][1], fa[mt][2], fa[mt][3], fb[nb][0], fb[nb][1]); mma8(d, fa[mt][4], fa[mt][5], fb[nb][2]);
                const float L2E = 1.4426950408889634f;
                o[2 * nb] = pack2(d[0] * L2E, d[1] * L2E); o[2 * nb + 1] = pack2(d[2] * L2E, d[3] * L2E);
            }
            asm volatile("stmatrix.sync.aligned.m8n8.x4.trans.shared.b16 [%0], {%1, %2, %3, %4};" :: "r"(o4 + mt * 2304), "r"(o[0]), "r"(o[1]), "r"(o[2]), "r"(o[3]) : "memory");
            asm volatile("stmatrix.sync.aligned.m8n8.x2.trans.shared.b16 [%0], {%1, %2};" :: "r"(r8 < 2 ? ob + 2048 + mt * 2304 : sb + B_HD + 20736), "r"(o[4]), "r"(o[5]) : "memory");
        }
        PST(19);
        wg_bar(wg);
        {
            const int mtx = tile >> 4, G8 = (tile >> 1) & 7, rq = 2 * (tile & 1) + c, cc = G8 >> 2, gi = (G8 & 3) ^ (2 * cc);
            uint8_t* dst = (uint8_t*)g_wimg + (cc * 108 + 36 * mtx + 18 * (gi & 1)) * 9216 + (gi >> 1) * 2304 + rq * 41472 + 3 * wg * 4608;
            uint4 v[4];
#pragma unroll
            for (int i = 0; i < 4; i++) if (i < 3 || t < 48)
                asm volatile("ld.shared.v4.u32 {%0, %1, %2, %3}, [%4];" : "=r"(v[i].x), "=r"(v[i].y), "=r"(v[i].z), "=r"(v[i].w) : "r"(sb + B_HD + 3 * wg * 2304 + (t + 128 * i) * 16));
#pragma unroll
            for (int i = 0; i < 4; i++) if (i < 3 || t < 48) {
                const int u = t + 128 * i, j = (u >= 144) + (u >= 288);
                *(uint4*)(dst + u * 16 + j * 2304) = v[i];
            }
        }
        __syncwarp();
        if (lead) mb_arrive(bb + FSIG);
    }
    PST(15);
    cf l[3], k[3];
    auto consts = [&]() {
    float lr, li, kr, ki;
    {
        const float a = bf2f(hre), b = bf2f(him), dt = __bfloat162float(__float2bfloat16(expf(bf2f(hdt))));
        const float e = expf(dt * a); float sn, cs;
        sincospif(dt * b * 0.31830988618379067f, &sn, &cs);
        lr = e * cs; li = e * sn;
        const float id = __fdividef(2.f, fmaf(a, a, b * b)), nr = lr - 1.f;
        kr = fmaf(nr, a, li * b) * id; ki = fmaf(li, a, -nr * b) * id;
    }
    if (swap) li = -li;
#pragma unroll
    for (int m = 0; m < 3; m++) {
        l[m] = {__shfl_sync(0xffffffffu, lr, m, 4), __shfl_sync(0xffffffffu, li, m, 4)};
        k[m] = {__shfl_sync(0xffffffffu, kr, m, 4), __shfl_sync(0xffffffffu, ki, m, 4)};
    }
    };
    if (wg) consts();
    else {
#pragma unroll
        for (int m = 0; m < 3; m++) asm volatile("{ .reg .f32 t; mov.f32 %0, t; mov.f32 %1, t; mov.f32 %2, t; mov.f32 %3, t; }" : "=f"(l[m].x), "=f"(l[m].y), "=f"(k[m].x), "=f"(k[m].y));
    }
    const uint32_t ep = get_epoch(bb) & 1;
    if (wg == 2 && t < 72) g_agg[ep ^ 1][(2 * tile + c) * 72 + t] = make_uint4(0, 0, 0, 0);
    cl_wait();
    PST(1);
    float acc[96];
    reg_def(acc);
    uint32_t prev = bb + DUMMY;
    if (wg) mb_wait(bb + TOK(wg - 1), 0);
    PST(17);
    {
        uint32_t par = 0, bar = bb + R1(3 - wg), alo = (SB0 >> 4) + (3 - wg) * 1536, xlo = (SB0 + B_X) >> 4;
        mb_wait(bar, 0);
#pragma unroll 1
        for (int kc = 0; kc < 9; kc++) {
            uint32_t nbar = bar + 16, nalo = alo + 1536, npar = par, xb = bb + (kc == 7 ? TOK(wg) : DUMMY);
            asm volatile("" : "+r"(xb));
            if (nbar == bb + R1(5)) { nbar = bb; nalo -= 5 * 1536; npar ^= 1; }
            st_b1<1>(acc, alo, DHI_SW, xlo, DHI_SW, kc, kc == 8 ? bar : nbar, kc == 8 ? par : npar, prev, xb, 0, lane);
            if (kc == 4 && wg == 0) mb_wait(bb + BXF, 0);
            prev = bar + 8; bar = nbar; alo = nalo; par = npar; xlo += 512;
        }
        wg_wait<0>(); reg_fence(acc);
        if (lead) { mb_arrive_n(prev, 2); if (wg == 2) mb_arrive_rem(rb + RFREE(0), 2); }
    }
    PST(2);
    if (wg == 0) consts();
    {
        cf l16[3], ex[3];
        const uint32_t t0 = scan_pass1<0>(acc, l[0], k[0], q, swap, l16[0], ex[0]), t1 = scan_pass1<32>(acc, l[1], k[1], q, swap, l16[1], ex[1]), t2 = scan_pass1<64>(acc, l[2], k[2], q, swap, l16[2], ex[2]);
        const uint8_t* ag = (const uint8_t*)(g_agg[ep] + (12 * c + warp) * 192);
        const uint8_t* pa = ag + tile * 64 + g * 8; const uint8_t* pb = ag + 2048 + tile * 32 + g * 4;
        if (q == 3) {
            asm volatile("st.relaxed.gpu.global.v2.b32 [%0], {%1, %2};" :: "l"(pa), "r"(t0), "r"(t1) : "memory");
            asm volatile("st.relaxed.gpu.global.b32 [%0], %1;" :: "l"(pb), "r"(t2) : "memory");
        }
#pragma unroll
        for (int m = 0; m < 3; m++) {
            float x, y;
            asm volatile("shfl.sync.up.b32 %0, %1, 1, 0x1c00, 0xffffffff;" : "=f"(x) : "f"(ex[m].x) : "memory"); asm volatile("shfl.sync.up.b32 %0, %1, 1, 0x1c00, 0xffffffff;" : "=f"(y) : "f"(ex[m].y) : "memory");
            ex[m] = csel(q >= 1, {x, y}, {0.f, 0.f});
        }
        scan_scale<0>(acc, k[0], swap); scan_scale<32>(acc, k[1], swap); scan_scale<64>(acc, k[2], swap);
        PST(3);
        uint32_t v[8][3];
#pragma unroll
        for (int i = 0; i < 8; i++) v[i][0] = v[i][1] = v[i][2] = 4 * i + q < tile ? 0u : 0x8000u;
        pa -= 64 * (q + 1); pb -= 32 * (q + 1);
        int rounds = 0;
        for (;;) {
            uint32_t miss = 0;
#pragma unroll
            for (int i = 0; i < 8; i++) agg_ld(v[i], pa - 256 * i, pb - 128 * i, miss);
            if (!__any_sync(0xffffffffu, miss)) break;
            if (rounds++) __nanosleep(150);
        }
        PST(4);
        if (wg == 2) wg_bar(2); else mb_wait(bb + (wg ? BXD : FRD), 0);
        const uint32_t ha = sb + B_HD + (8 * w + g) * 128, h0 = ha + ((2 * q) ^ g) * 16, h1 = ha + ((2 * q + 1) ^ g) * 16;
        const uint32_t o0 = wg == 1 ? 20480 : wg * 24576, o1 = wg == 1 ? 32768 : o0 + 4096, o2 = wg == 1 ? 36864 : o0 + 16384;
        scan_pass2<0>(acc, l[0], l16[0], v, ex[0], q, h0 + o0, h1 + o0, 8192);
        scan_pass2<1>(acc, l[1], l16[1], v, ex[1], q, h0 + o1, h1 + o1, 8192);
        scan_pass2<2>(acc, l[2], l16[2], v, ex[2], q, h0 + o2, h1 + o2, wg == 2 ? 4096 : 8192);
        proxy_fence(); __syncwarp();
        if (lead) mb_arrive(bb + HR(wg));
        PST(5);
    }
    const int row = 64 * tile + 16 * w + g, col = 288 * c + 96 * wg + 4 * q;
    const uint32_t hlo = (SB0 + B_HD) >> 4, blo = SB0 >> 4, ko = 4 * c;
    uint32_t xd[24];
    b_load_xd(xd, P, row, col);
    float* op = P.out + (size_t)row * 1152 + 576 + col;
    if (wg < 2) {
#pragma unroll
        for (int i = 0; i < 48; i++) asm volatile("mov.b32 %0, 0;" : "=f"(acc[i]));
        b_init_xd<48>(acc, xd);
        mb_wait(bb + TOK(2 + wg), 0);
        if (wg == 0) mb_wait(bb + HR(0), 0);
        PST(11);
        b2_run<0, 6>(acc, bb, wg, wg, TOK(3 + wg), prev, lane);
        wg_wait<0>();
        if (lead) mb_arrive_n(prev, 2);
        PST(6);
        mb_wait(bb + TOK(4 + wg), 0);
        if (wg == 0) mb_wait(bb + HR(2), 0);
        PST(7);
        b2_run<6, 8>(acc, bb, 2 - wg, wg, DUMMY, prev, lane);
        const uint32_t s8 = 4 - wg, s9 = 4 * wg;
        st_b2e<1>(acc, hlo + 4096, DHI_SW, blo + s8 * 1536 + ko, DHI_SW, 1, bb + R1(s9), 1, prev, bb + TOK(5 + wg), 0, lane);
        st_b2e<0>(acc, hlo + 4352, DHI_SW, blo + s9 * 1536 + ko, DHI_SW, 1, bb + R1(s9), 1, bb + R1(s8) + 8, 0, 0, lane);
        wg_wait<0>(); reg_fence(acc);
        if (lead) mb_arrive_n(bb + R1(s9) + 8, 2);
        PST(12);
        mb_wait(bb + RFREE(0), 0);
        b_send<0, 6>(acc, rsb, wg, t);
        b_out<48>(acc, sb, wg, t, op);
    } else {
        float as[48], af[48];
        reg_def(as);
        b_init_xd<0>(af, xd);
        prev = bb + DUMMY;
        mb_wait(bb + TOK(6), 0);
        PST(11);
        mb_wait(bb + R1(0), 0);
#pragma unroll 1
        for (int u = 0; u < 4; u++) { st_b2s<0>(as, hlo + u * 1024, DHI_SW, blo + u * 1536, DHI_SW, u, bb + R1(u + 1), 0, prev, 0, 0, lane); prev = bb + R1(u) + 8; }
        st_b2t<0>(as, hlo + 4096, DHI_SW, blo + 4 * 1536 + ko, DHI_SW, 1, bb, 1, prev, 0, 0, lane);
        st_b2s<0>(af, hlo, DHI_SW, blo, DHI_SW, 1, bb + R1(1), 1, bb + R1(4) + 8, 0, 0, lane);
        reg_fence(as);
        PST(6);
        mb_wait(bb + RFREE(1), 0);
        PST(7);
        b_send<0, 3>(as, rsb, 2, t);
        st_b2s<0>(af, hlo + 1024, DHI_SW, blo + 1536, DHI_SW, 1, bb + R1(2), 1, bb + DUMMY, 0, 0, lane);
        b_send<3, 6>(as, rsb, 2, t);
        st_b2s<0>(af, hlo + 2048, DHI_SW, blo + 2 * 1536, DHI_SW, 1, bb + R1(3), 1, bb + DUMMY, 0, 0, lane);
        st_b2s<0>(af, hlo + 3072, DHI_SW, blo + 3 * 1536, DHI_SW, 1, bb + R1(4), 1, bb + DUMMY, 0, 0, lane);
        st_b2t<0>(af, hlo + 4096, DHI_SW, blo + 4 * 1536 + ko, DHI_SW, 1, bb + R1(4), 1, bb + DUMMY, 0, 0, lane);
        wg_wait<0>(); reg_fence(af);
        PST(12);
        b_out<0>(af, sb, wg, t, op);
    }
}

__global__ void __launch_bounds__(512, 1) fused_kernel(const __grid_constant__ Params P) {
    extern __shared__ __align__(1024) uint8_t smem_raw[];
    uint32_t sb = (uint32_t)__cvta_generic_to_shared(smem_raw);
    asm volatile("mov.b32 %0, %0;" : "+r"(sb));
    const int warp = __shfl_sync(0xffffffffu, threadIdx.x >> 5, 0);
    const int c = blockIdx.x & 1, isb = blockIdx.x >> 6, tile = (blockIdx.x >> 1) & 31;
    const uint32_t bb = sb + BAR;
    if (warp >= 12) {
        asm volatile("setmaxnreg.dec.sync.aligned.u32 32;");
        if (warp == 12) { e_init(bb + R1(3), 1); e_init(bb + R1(3) + 8, 8); e_init(bb + FLD, 1); }
        else if (warp == 13) {
            pf_map(&P.m[10 * isb]); pf_map(&P.m[1 + 3 * isb]); pf_map(&P.m[isb ? 5 : 2 + c]);
            if (isb) { pf_map(&P.m[6 + c]); pf_map(&P.m[8 + c]); }
            e_init(bb + DUMMY, 1u << 19); e_init(bb + AXF(0), 1); e_init(bb + AXF(1), 1);
        } else if (warp == 14) { e_init(bb + VST, 8); e_init(bb + VST + 8, 8); e_init(bb + VST + 16, 8); e_init(bb + FSIG, 12); }
        else {
            if (sb != (SB0 | ((uint32_t)c << 24))) asm volatile("trap;");
            e_init(bb + XD(0), 16); e_init(bb + XD(1), 16); e_init(bb + DONE, 15);
        }
        asm volatile("fence.mbarrier_init.release.cluster;" ::: "memory");
        if (warp > 12) cta_sync();
        if (isb) b_producer(P, sb, warp - 12, c, tile); else a_producer(P, sb, warp - 12, c, tile);
        cl_wait();
        cl_arrive();
        if (warp == 15) mb_wait_b(bb + DONE); else e_arrive(bb + DONE, 1);
        cl_wait();
    } else {
        if (warp < 10 && elect_one()) {
            const uint32_t ce = warp < 5 || warp > 7 ? 1 : 4, co = warp < 2 ? 8 : (warp < 8 ? 4 : 1), b0 = bb + 64 * warp;
#pragma unroll
            for (int j = 0; j < 4; j++) if (j < 3 || warp > 1) { mb_init(b0 + 16 * j, ce); mb_init(b0 + 16 * j + 8, co); }
            if (warp == 0) {
#pragma unroll
                for (int j = 0; j < 3; j++) { mb_arrive(bb + R1(j)); mb_arrive_n(bb + R1(j) + 8, 8); }
            }
            asm volatile("fence.mbarrier_init.release.cluster;" ::: "memory");
        }
        __syncwarp();
        asm volatile("setmaxnreg.inc.sync.aligned.u32 160;");
        if (isb) b_consumer(P, sb, warp, c, tile); else a_consumer(P, sb, warp, c, tile);
        __syncwarp();
        e_arrive(bb + DONE, 1);
        cl_wait();
    }
}

typedef CUresult (*EncodeTiledFn)(CUtensorMap*, CUtensorMapDataType, cuuint32_t, void*, const cuuint64_t*, const cuuint64_t*, const cuuint32_t*, const cuuint32_t*,
                                  CUtensorMapInterleave, CUtensorMapSwizzle, CUtensorMapL2promotion, CUtensorMapFloatOOBfill);

extern "C" void kernel_launch(void* const* d_in, const int* in_sizes, int n_in, void* d_out, int out_size) {
    static EncodeTiledFn enc = nullptr;
    if (!enc) {
        void* fn = nullptr; cudaDriverEntryPointQueryResult qr;
        cudaGetDriverEntryPoint("cuTensorMapEncodeTiled", &fn, cudaEnableDefault, &qr);
        enc = (EncodeTiledFn)fn;
        cudaFuncSetAttribute(fused_kernel, cudaFuncAttributeMaxDynamicSharedMemorySize, 232448);
    }
    Params P;
    const cuuint32_t es[5] = {1, 1, 1, 1, 1};
    auto mk = [&](int i, void* base, int rank, const cuuint64_t* gd, const cuuint64_t* gs, const cuuint32_t* bd) {
        enc(&P.m[i], CU_TENSOR_MAP_DATA_TYPE_BFLOAT16, rank, base, gd, gs, bd, es, CU_TENSOR_MAP_INTERLEAVE_NONE, CU_TENSOR_MAP_SWIZZLE_128B,
            CU_TENSOR_MAP_L2_PROMOTION_L2_128B, CU_TENSOR_MAP_FLOAT_OOB_FILL_NONE);
    };
    { const cuuint64_t gd[2] = {576, 2048}, gs[1] = {1152}; const cuuint32_t bd[2] = {64, 64}; mk(0, d_in[0], 2, gd, gs, bd); }
    { const cuuint64_t gd[3] = {64, 576, 27}, gs[2] = {3456, 128}; const cuuint32_t bd[3] = {64, 32, 2}; mk(1, d_in[1], 3, gd, gs, bd); }
    for (int c = 0; c < 2; c++) { const cuuint64_t gd[2] = {(cuuint64_t)(c ? 1472 : 1440), 576}, gs[1] = {3456}; const cuuint32_t bd[2] = {64, 32}; mk(2 + c, d_in[1], 2, gd, gs, bd); }
    { const cuuint64_t gd[5] = {576, 2, 4, 8, 32}, gs[4] = {1152, 16 * 1152, 2 * 1152, 64 * 1152}; const cuuint32_t bd[5] = {64, 2, 4, 8, 1}; mk(4, d_in[4], 5, gd, gs, bd); }
    const uintptr_t bre = (uintptr_t)d_in[7], bim = (uintptr_t)d_in[8];
    P.swap = bim < bre;
    { const cuuint64_t gd[4] = {576, 8, 2, 72}, gs[3] = {1152, (cuuint64_t)(P.swap ? bre - bim : bim - bre), 8 * 1152}; const cuuint32_t bd[4] = {64, 8, 2, 4};
      mk(5, P.swap ? d_in[8] : d_in[7], 4, gd, gs, bd); }
    for (int im = 0; im < 2; im++) for (int c = 0; c < 2; c++) {
        const cuuint64_t gd[5] = {288, 2, 4, 2, 36}, gs[4] = {1152, 4 * 1152, 2 * 1152, 16 * 1152}; const cuuint32_t bd[5] = {64, 2, 4, 2, 6};
        mk(6 + 2 * im + c, (uint8_t*)d_in[9 + im] + 576 * c, 5, gd, gs, bd);
    }
    { const cuuint64_t gd[2] = {1728, 576}, gs[1] = {3456}; const cuuint32_t bd[2] = {72, 144};
      enc(&P.m[10], CU_TENSOR_MAP_DATA_TYPE_BFLOAT16, 2, d_in[1], gd, gs, bd, es, CU_TENSOR_MAP_INTERLEAVE_NONE, CU_TENSOR_MAP_SWIZZLE_NONE, CU_TENSOR_MAP_L2_PROMOTION_L2_128B, CU_TENSOR_MAP_FLOAT_OOB_FILL_NONE); }
    P.wphi = (const uint8_t*)d_in[2]; P.wo = (const uint32_t*)d_in[3];
    P.xb = (const uint2*)d_in[4]; P.lre = (const unsigned short*)d_in[5]; P.lim = (const unsigned short*)d_in[6]; P.ldt = (const unsigned short*)d_in[11]; P.dsk = (const uint2*)d_in[12];
    for (int c = 0; c < 2; c++) for (int n = 0; n < 30; n++) {
        const int r = n < 20 ? (n < 12 ? n >= 6 : n >= 16) : 2, u = n - (n < 6 ? 0 : (n < 16 ? 6 : (n < 20 ? 10 : 20))), ys = 3 - 3 * c + r, yf = 3 * c + r;
        const int j = r < 2 ? u >> 1 : (u < 5 ? u : u - 5), k0 = j < 4 ? 32 * c + 64 * j : (c ? -32 : 256);
        const int i0 = r < 2 ? u & 1 : 0, i1 = r < 2 ? u & 1 : 1, y0 = r < 2 || u < 5 ? ys : yf, y1 = r == 2 && u < 5 ? ys : yf;
        P.b2[c][n] = (uint32_t)(k0 + 32) << 16 | (uint32_t)(6 * y1) << 10 | (uint32_t)(6 * y0) << 4 | i1 << 2 | i0 << 1;
    }
    P.cw[0] = (const uint8_t*)d_in[9]; P.cw[1] = (const uint8_t*)d_in[10];
    P.out = (float*)d_out;
    cudaLaunchConfig_t cfg = {};
    cfg.gridDim = dim3(128); cfg.blockDim = dim3(512); cfg.dynamicSmemBytes = 232448; cfg.stream = cudaStreamPerThread;
    cudaLaunchAttribute at[1];
    at[0].id = cudaLaunchAttributeClusterDimension; at[0].val.clusterDim.x = 2; at[0].val.clusterDim.y = 1; at[0].val.clusterDim.z = 1;
    cfg.attrs = at; cfg.numAttrs = 1;
    cudaLaunchKernelEx(&cfg, fused_kernel, P);
}
```
